```python
import torch

def _softmax(x, axis=-1):
    return torch.softmax(x, dim=axis)
def _gelu(x):
    return torch.nn.functional.gelu(x, approximate="tanh")
def _silu(x):
    return torch.nn.functional.silu(x)
def _sigmoid(x):
    return torch.sigmoid(x)
def _layernorm(x, axis=-1, eps=1e-5):
    m = x.mean(dim=axis, keepdim=True)
    v = x.var(dim=axis, keepdim=True, unbiased=False)
    return (x - m) / torch.sqrt(v + eps)
def _scatter_add(tgt, idx, src, axis=0):
    return tgt.clone().index_add_(axis, idx, src)
def _segment_sum(src, seg, n):
    out = torch.zeros((n,) + src.shape[1:], dtype=src.dtype)
    return out.index_add_(0, seg, src)
def _pad(x, pw):
    flat = tuple(v for pair in reversed(pw) for v in pair)
    return torch.nn.functional.pad(x, flat)

kernel_name = 'concat_heads__ssm_conv_h3__sliding_block__prompt'

def setup_inputs():

    _w = (lambda a: (lambda t: t.to(torch.bfloat16) if t.is_floating_point() else t)(torch.as_tensor(a)))
    def _A_setup():
        B, S, D = 1, 2048, 640
        ks = 4
        return {
            "q": _w((lambda *s: torch.randn(*s, dtype=torch.bfloat16) * 0.05)(B, S, D)),
            "k": _w((lambda *s: torch.randn(*s, dtype=torch.bfloat16) * 0.8)(B, S, D)),
            "v": _w((lambda *s: torch.randn(*s, dtype=torch.bfloat16) * 0.8)(B, S, D)),
            "shift_k": _w((lambda *s: torch.randn(*s, dtype=torch.bfloat16) * 0.8)(D, ks) * 0.5),
            "ssm_k": _w((lambda *s: torch.randn(*s, dtype=torch.bfloat16) * 3.2)(D, S) * (1.0 / S ** 0.5)),
            "ssm_D": _w((lambda *s: torch.randn(*s, dtype=torch.bfloat16) * 0.8)(D)),
        }
    _A_in = _A_setup()

    def _B_setup():
        B, S, D = 1, 2048, 640
        return {
            "x": _w((lambda *s: torch.randn(*s, dtype=torch.bfloat16) * 0.2)(B, S, D)),
            "wqkv": _w((lambda *s: torch.randn(*s, dtype=torch.bfloat16) * 0.2)(D, 3 * D)),
            "wo": _w((lambda *s: torch.randn(*s, dtype=torch.bfloat16) * 0.05)(D, D)),
        }
    _B_in = _B_setup()

    return {
        "A_q": _A_in["q"],
        "A_k": _A_in["k"],
        "A_v": _A_in["v"],
        "A_shift_k": _A_in["shift_k"],
        "A_ssm_k": _A_in["ssm_k"],
        "A_ssm_D": _A_in["ssm_D"],
        "B_x": _B_in["x"],
        "B_wqkv": _B_in["wqkv"],
        "B_wo": _B_in["wo"],
    }

def reference(A_q, A_k, A_v, A_shift_k, A_ssm_k, A_ssm_D, B_x, B_wqkv, B_wo):
    def _A_ref(q, k, v, shift_k, ssm_k, ssm_D):
        B, S, D = q.shape
        ks = shift_k.shape[-1]
        k_pad = _pad(k, ((0, 0), (ks - 1, 0), (0, 0)))
        k_shift = torch.zeros_like(k)
        for t in range(ks):
            k_shift = k_shift + k_pad[:, t:t + S, :] * shift_k[:, ks - 1 - t][None, None, :]
        kv = k_shift * v
        L = 2 * S
        kv_pad = _pad(kv, ((0, 0), (0, S), (0, 0)))
        kf_pad = _pad(ssm_k, ((0, 0), (0, S)))
        kv_f = (lambda x, axes=(-2,-1): torch.fft.rfft2(x.float(), dim=axes))(kv_pad[:, None, :, :], axes=(1, 2))
        kf_f = (lambda x, axes=(-2,-1): torch.fft.rfft2(x.float(), dim=axes))(kf_pad[:, None, :], axes=(1, 2))
        kf_f = (lambda x, *d: x.permute(*d))(kf_f, 1, 2, 0)
        y_f = kv_f * kf_f[None, :, :, :]
        y = (lambda x, s, axes=(-2,-1): torch.fft.irfft2(x, s=s, dim=axes).to(torch.bfloat16))(y_f, (1, L), axes=(1, 2))[:, 0, :S, :]
        y = y + kv * ssm_D[None, None, :]
        return q * y

    def _B_ref(x, wqkv, wo):
        B, S, D = x.shape
        H = 32; Dh = D // H; W = 256
        qkv = (lambda x, *d: x.permute(*d))((x @ wqkv).reshape(B, S, 3, H, Dh), 2, 0, 3, 1, 4)
        q, k, v = qkv[0], qkv[1], qkv[2]
        scores = torch.einsum("bhqd,bhkd->bhqk", q, k) * (Dh ** -0.5)
        idx = torch.arange(S)
        mask = (idx[:, None] - idx[None, :] >= 0) & (idx[:, None] - idx[None, :] < W)
        scores = torch.where(mask[None, None], scores, -1e9)
        p = _softmax(scores, axis=-1)
        o = torch.einsum("bhqk,bhkd->bhqd", p, v)
        return (lambda x, *d: x.permute(*d))(o, 0, 2, 1, 3).reshape(B, S, D) @ wo

    a = _A_ref(A_q, A_k, A_v, A_shift_k, A_ssm_k, A_ssm_D)
    b = _B_ref(B_x, B_wqkv, B_wo)
    return torch.concatenate([a, b], axis=-1)
```

```cpp
#include <cuda_runtime.h>
#include <cuda_bf16.h>
#include <cuda.h>
#include <stdint.h>

namespace {

constexpr int kS = 2048;
constexpr int kNumCta = 128;
constexpr int kThreads = 512;

__device__ __align__(1024) uint8_t g_kv[32 * 16 * 10240];
__device__ __align__(1024) uint8_t g_o[16 * 2 * 80 * 1024];
__device__ __align__(1024) uint8_t g_xt[640 * 4096];
__device__ __align__(1024) uint8_t g_zt[640 * 4096];
__device__ __align__(1024) uint8_t g_wo[8 * 102400];
__device__ unsigned g_cnt[928 * 32];
__device__ unsigned g_ticket[96];

constexpr int CNT_KV = 0;
constexpr int CNT_PREP = 512;
constexpr int CNT_CONV = 520;
constexpr int CNT_WO = 528;
constexpr int CNT_ATT = 536;

constexpr uint32_t kSmemBase = 1024;
constexpr uint32_t SM_STAGE = 47104;
constexpr uint32_t SM_HR = 36864;
constexpr uint32_t HR_OWN = 6144, HR_R2 = 16384, HR_R1 = 26624;
constexpr uint32_t SM_E = 147456;
constexpr uint32_t SM_C = 167936;
constexpr uint32_t SM_CX = SM_C;
constexpr uint32_t SM_CH = SM_C + 8704;
constexpr uint32_t SM_CZ = SM_C + 25344;
constexpr uint32_t SM_CR = SM_C + 29440;
constexpr uint32_t SM_CQ = SM_C + 40960;
constexpr uint32_t SM_CSTG = SM_C + 41984;
constexpr uint32_t SM_BAR = SM_C + 63360;
constexpr uint32_t SM_ZERO = SM_BAR + 448;
constexpr uint32_t SM_TOTAL = SM_BAR + 512;

__device__ __forceinline__ uint32_t wo_part_off(int i) {
  return (uint32_t)((i & 1) * 12800 + (i < 2 ? 0 : i < 4 ? 73728 : i < 6 ? 25600 : 99328));
}
__device__ __forceinline__ uint32_t o_tile_off(int i) {
  return (i == 0 || i == 3 || i == 6) ? 51200u : (i == 1 || i == 4) ? 124928u : (i == 2 || i == 5) ? SM_E : 0u;
}

enum {
  B_FULL = 0,
  B_EMPTY = 3,
  B_GEMMD = 6,
  B_EPI = 7,
  B_REM = 8,
  B_H1ST = 12,
  B_ATTD = 13,
  B_OST = 14,
  B_WOF = 17,
  B_GO = 19,
  B_GO0 = 20,
  B_KV = 21,
  B_X = 22,
  B_FIN = 24,
  B_OE = 25,
  B_OF = 33,
  B_COUNT = 49
};

__device__ __forceinline__ uint32_t smem_u32(const void* p) { return (uint32_t)__cvta_generic_to_shared(p); }

__device__ __forceinline__ void mbar_init(uint32_t bar, uint32_t count) {
  asm volatile("mbarrier.init.shared::cta.b64 [%0], %1;" ::"r"(bar), "r"(count) : "memory");
}
__device__ __forceinline__ void mbar_expect_tx(uint32_t bar, uint32_t bytes) {
  asm volatile("mbarrier.arrive.expect_tx.shared::cta.b64 _, [%0], %1;" ::"r"(bar), "r"(bytes) : "memory");
}
__device__ __forceinline__ void mbar_arrive(uint32_t bar) {
  asm volatile("mbarrier.arrive.shared::cta.b64 _, [%0];" ::"r"(bar) : "memory");
}
__device__ __forceinline__ void wait_timeout_trap() { __trap(); }
__device__ __forceinline__ void mbar_wait(uint32_t bar, uint32_t parity) {
  asm volatile(
      "{\n.reg .pred p;\n.reg .u32 c;\nmov.u32 c, 0;\n"
      "LAB_WAIT:\nmbarrier.try_wait.parity.shared::cta.b64 p, [%0], %1;\n@p bra DONE;\n"
      "add.u32 c, c, 1;\nsetp.lt.u32 p, c, 0x40000;\n@p bra LAB_WAIT;\nDONE:\n}\n" ::"r"(bar),
      "r"(parity)
      : "memory");
}
__device__ __forceinline__ unsigned ld_acquire(const unsigned* p) {
  unsigned v;
  asm volatile("ld.acquire.gpu.global.u32 %0, [%1];" : "=r"(v) : "l"(p) : "memory");
  return v;
}
__device__ __forceinline__ void red_relaxed(unsigned* p, unsigned v) {
  asm volatile("red.relaxed.gpu.global.add.u32 [%0], %1;" ::"l"(p), "r"(v) : "memory");
}
__device__ __forceinline__ void wait_counter(const unsigned* p, unsigned target) {
  uint32_t spins = 0;
  while ((int)(ld_acquire(p) - target) < 0) {
    if (++spins > (1u << 20)) wait_timeout_trap();
  }
}
__device__ __forceinline__ void fence_async_global() { asm volatile("fence.proxy.async.global;" ::: "memory"); }
__device__ __forceinline__ void fence_release() { asm volatile("fence.acq_rel.gpu;" ::: "memory"); }
__device__ __forceinline__ void fence_async_smem() { asm volatile("fence.proxy.async.shared::cta;" ::: "memory"); }

__device__ __forceinline__ void tma_load_2d(uint32_t dst, const CUtensorMap* tm, int c0, int c1, uint32_t bar) {
  asm volatile(
      "cp.async.bulk.tensor.2d.shared::cluster.global.mbarrier::complete_tx::bytes [%0], [%1, {%3, %4}], [%2];" ::"r"(dst),
      "l"(tm), "r"(bar), "r"(c0), "r"(c1)
      : "memory");
}
__device__ __forceinline__ void tma_load_3d(uint32_t dst, const CUtensorMap* tm, int c0, int c1, int c2, uint32_t bar) {
  asm volatile(
      "cp.async.bulk.tensor.3d.shared::cluster.global.mbarrier::complete_tx::bytes [%0], [%1, {%3, %4, %5}], [%2];" ::"r"(dst),
      "l"(tm), "r"(bar), "r"(c0), "r"(c1), "r"(c2)
      : "memory");
}
__device__ __forceinline__ uint4 ldg_stream(const void* p) {
  uint4 v;
  asm volatile("ld.global.nc.L1::no_allocate.v4.b32 {%0,%1,%2,%3}, [%4];" : "=r"(v.x), "=r"(v.y), "=r"(v.z), "=r"(v.w) : "l"(p));
  return v;
}
__device__ __forceinline__ void tma_store_2d(const CUtensorMap* tm, int c0, int c1, uint32_t src) {
  asm volatile("cp.async.bulk.tensor.2d.global.shared::cta.bulk_group [%0, {%2, %3}], [%1];" ::"l"(tm), "r"(src),
               "r"(c0), "r"(c1)
               : "memory");
}
__device__ __forceinline__ void tma_store_3d(const CUtensorMap* tm, int c0, int c1, int c2, uint32_t src) {
  asm volatile("cp.async.bulk.tensor.3d.global.shared::cta.bulk_group [%0, {%2, %3, %4}], [%1];" ::"l"(tm), "r"(src),
               "r"(c0), "r"(c1), "r"(c2)
               : "memory");
}
__device__ __forceinline__ void lds128(uint32_t a, uint32_t& v0, uint32_t& v1, uint32_t& v2, uint32_t& v3);
template <int BYTES>
__device__ __forceinline__ void warp_copy_out(uint8_t* dst, uint32_t src, int lane) {
  static_assert(BYTES % 2560 == 0, "five 512-byte rows per round");
#pragma unroll 1
  for (int o = 0; o < BYTES; o += 2560) {
    uint4 v[5];
#pragma unroll
    for (int i = 0; i < 5; i++) lds128(src + o + i * 512 + lane * 16, v[i].x, v[i].y, v[i].z, v[i].w);
#pragma unroll
    for (int i = 0; i < 5; i++) *reinterpret_cast<uint4*>(dst + o + i * 512 + lane * 16) = v[i];
  }
}
__device__ __forceinline__ void bulk_load(uint32_t dst, const void* src, uint32_t bytes, uint32_t bar) {
  asm volatile("cp.async.bulk.shared::cluster.global.mbarrier::complete_tx::bytes [%0], [%1], %2, [%3];" ::"r"(dst),
               "l"(src), "r"(bytes), "r"(bar)
               : "memory");
}
__device__ __forceinline__ void bulk_store(void* dst, uint32_t src, uint32_t bytes) {
  asm volatile("cp.async.bulk.global.shared::cta.bulk_group [%0], [%1], %2;" ::"l"(dst), "r"(src), "r"(bytes) : "memory");
}
__device__ __forceinline__ void bulk_commit() { asm volatile("cp.async.bulk.commit_group;" ::: "memory"); }
template <int N>
__device__ __forceinline__ void bulk_wait() {
  asm volatile("cp.async.bulk.wait_group %0;" ::"n"(N) : "memory");
}
template <int N>
__device__ __forceinline__ void bulk_wait_read() {
  asm volatile("cp.async.bulk.wait_group.read %0;" ::"n"(N) : "memory");
}
__device__ __forceinline__ void l2_prefetch(const void* p, uint32_t bytes) {
  asm volatile("cp.async.bulk.prefetch.L2.global [%0], %1;" ::"l"(p), "r"(bytes) : "memory");
}
__device__ __forceinline__ void tma_prefetch_2d(const CUtensorMap* tm, int c0, int c1) {
  asm volatile("cp.async.bulk.prefetch.tensor.2d.L2.global [%0, {%1, %2}];" ::"l"(tm), "r"(c0), "r"(c1) : "memory");
}
__device__ __forceinline__ void tma_prefetch_3d(const CUtensorMap* tm, int c0, int c1, int c2) {
  asm volatile("cp.async.bulk.prefetch.tensor.3d.L2.global [%0, {%1, %2, %3}];" ::"l"(tm), "r"(c0), "r"(c1), "r"(c2) : "memory");
}
__device__ __forceinline__ void prefetch_tmap(const CUtensorMap* tm) {
  asm volatile("prefetch.tensormap [%0];" ::"l"(tm) : "memory");
}
__device__ __forceinline__ void named_sync(int id, int n) { asm volatile("bar.sync %0, %1;" ::"r"(id), "r"(n) : "memory"); }
__device__ __forceinline__ bool named_sync_or(int id, int n, bool pred) {
  uint32_t r;
  asm volatile(
      "{\n.reg .pred p, q;\nsetp.ne.u32 q, %3, 0;\nbarrier.cta.red.or.pred p, %1, %2, q;\nselp.u32 %0, 1, 0, p;\n}\n"
      : "=r"(r)
      : "r"(id), "r"(n), "r"((uint32_t)pred)
      : "memory");
  return r != 0;
}

__device__ __forceinline__ void wg_fence() { asm volatile("wgmma.fence.sync.aligned;" ::: "memory"); }
__device__ __forceinline__ void wg_commit() { asm volatile("wgmma.commit_group.sync.aligned;" ::: "memory"); }
template <int N>
__device__ __forceinline__ void wg_wait() {
  asm volatile("wgmma.wait_group.sync.aligned %0;" ::"n"(N) : "memory");
}
template <int N>
__device__ __forceinline__ void fence_regs(float (&d)[N]) {
#pragma unroll
  for (int i = 0; i < N; i++) asm volatile("" : "+f"(d[i])::"memory");
}
template <int N>
__device__ __forceinline__ void fence_regs(uint32_t (&d)[N]) {
#pragma unroll
  for (int i = 0; i < N; i++) asm volatile("" : "+r"(d[i])::"memory");
}
__device__ __forceinline__ uint64_t make_desc(uint32_t addr, uint32_t lbo, uint32_t sbo, uint32_t swz) {
  uint64_t d = (uint64_t)((addr & 0x3FFFF) >> 4);
  d |= (uint64_t)((lbo & 0x3FFFF) >> 4) << 16;
  d |= (uint64_t)((sbo & 0x3FFFF) >> 4) << 32;
  d |= (uint64_t)swz << 62;
  return d;
}

template <uint32_t HI>
static __device__ __forceinline__ void wgmma_rsl_n192_tb(float (&d)[96], uint32_t a0, uint32_t a1, uint32_t a2, uint32_t a3, uint32_t dlo, int scale_d) {
  asm volatile("{\n.reg .pred p;\n.reg .b64 db;\nsetp.ne.b32 p, %101, 0;\nmov.b64 db, {%100, %102};\n"
    "wgmma.mma_async.sync.aligned.m64n192k16.f32.bf16.bf16 "
    "{%0, %1, %2, %3, %4, %5, %6, %7, %8, %9, %10, %11, %12, %13, %14, %15, %16, %17, %18, %19, %20, %21, %22, %23, %24, %25, %26, %27, %28, %29, %30, %31, %32, %33, %34, %35, %36, %37, %38, %39, %40, %41, %42, %43, %44, %45, %46, %47, %48, %49, %50, %51, %52, %53, %54, %55, %56, %57, %58, %59, %60, %61, %62, %63, %64, %65, %66, %67, %68, %69, %70, %71, %72, %73, %74, %75, %76, %77, %78, %79, %80, %81, %82, %83, %84, %85, %86, %87, %88, %89, %90, %91, %92, %93, %94, %95}, "
    "{%96,%97,%98,%99}, db, p, 1, 1, 1;\n}\n"
    :
      "+f"(d[0]), "+f"(d[1]), "+f"(d[2]), "+f"(d[3]), "+f"(d[4]), "+f"(d[5]), "+f"(d[6]), "+f"(d[7]),
      "+f"(d[8]), "+f"(d[9]), "+f"(d[10]), "+f"(d[11]), "+f"(d[12]), "+f"(d[13]), "+f"(d[14]), "+f"(d[15]),
      "+f"(d[16]), "+f"(d[17]), "+f"(d[18]), "+f"(d[19]), "+f"(d[20]), "+f"(d[21]), "+f"(d[22]), "+f"(d[23]),
      "+f"(d[24]), "+f"(d[25]), "+f"(d[26]), "+f"(d[27]), "+f"(d[28]), "+f"(d[29]), "+f"(d[30]), "+f"(d[31]),
      "+f"(d[32]), "+f"(d[33]), "+f"(d[34]), "+f"(d[35]), "+f"(d[36]), "+f"(d[37]), "+f"(d[38]), "+f"(d[39]),
      "+f"(d[40]), "+f"(d[41]), "+f"(d[42]), "+f"(d[43]), "+f"(d[44]), "+f"(d[45]), "+f"(d[46]), "+f"(d[47]),
      "+f"(d[48]), "+f"(d[49]), "+f"(d[50]), "+f"(d[51]), "+f"(d[52]), "+f"(d[53]), "+f"(d[54]), "+f"(d[55]),
      "+f"(d[56]), "+f"(d[57]), "+f"(d[58]), "+f"(d[59]), "+f"(d[60]), "+f"(d[61]), "+f"(d[62]), "+f"(d[63]),
      "+f"(d[64]), "+f"(d[65]), "+f"(d[66]), "+f"(d[67]), "+f"(d[68]), "+f"(d[69]), "+f"(d[70]), "+f"(d[71]),
      "+f"(d[72]), "+f"(d[73]), "+f"(d[74]), "+f"(d[75]), "+f"(d[76]), "+f"(d[77]), "+f"(d[78]), "+f"(d[79]),
      "+f"(d[80]), "+f"(d[81]), "+f"(d[82]), "+f"(d[83]), "+f"(d[84]), "+f"(d[85]), "+f"(d[86]), "+f"(d[87]),
      "+f"(d[88]), "+f"(d[89]), "+f"(d[90]), "+f"(d[91]), "+f"(d[92]), "+f"(d[93]), "+f"(d[94]), "+f"(d[95])
    : "r"(a0), "r"(a1), "r"(a2), "r"(a3), "r"(dlo), "r"(scale_d), "n"(HI));
}

template <uint32_t HI>
static __device__ __forceinline__ void wgmma_rsl_n48_tb(float (&d)[24], uint32_t a0, uint32_t a1, uint32_t a2, uint32_t a3, uint32_t dlo, int scale_d) {
  asm volatile("{\n.reg .pred p;\n.reg .b64 db;\nsetp.ne.b32 p, %29, 0;\nmov.b64 db, {%28, %30};\n"
    "wgmma.mma_async.sync.aligned.m64n48k16.f32.bf16.bf16 "
    "{%0, %1, %2, %3, %4, %5, %6, %7, %8, %9, %10, %11, %12, %13, %14, %15, %16, %17, %18, %19, %20, %21, %22, %23}, "
    "{%24,%25,%26,%27}, db, p, 1, 1, 1;\n}\n"
    :
      "+f"(d[0]), "+f"(d[1]), "+f"(d[2]), "+f"(d[3]), "+f"(d[4]), "+f"(d[5]), "+f"(d[6]), "+f"(d[7]),
      "+f"(d[8]), "+f"(d[9]), "+f"(d[10]), "+f"(d[11]), "+f"(d[12]), "+f"(d[13]), "+f"(d[14]), "+f"(d[15]),
      "+f"(d[16]), "+f"(d[17]), "+f"(d[18]), "+f"(d[19]), "+f"(d[20]), "+f"(d[21]), "+f"(d[22]), "+f"(d[23])
    : "r"(a0), "r"(a1), "r"(a2), "r"(a3), "r"(dlo), "r"(scale_d), "n"(HI));
}

static __device__ __forceinline__ void wgmma_ss_n80_tb(float (&d)[40], uint64_t da, uint64_t db, int scale_d) {
  asm volatile("{\n.reg .pred p;\nsetp.ne.b32 p, %42, 0;\n"
    "wgmma.mma_async.sync.aligned.m64n80k16.f32.bf16.bf16 "
    "{%0, %1, %2, %3, %4, %5, %6, %7, %8, %9, %10, %11, %12, %13, %14, %15, %16, %17, %18, %19, %20, %21, %22, %23, %24, %25, %26, %27, %28, %29, %30, %31, %32, %33, %34, %35, %36, %37, %38, %39}, "
    "%40, %41, p, 1, 1, 0, 1;\n}\n"
    :
      "+f"(d[0]), "+f"(d[1]), "+f"(d[2]), "+f"(d[3]), "+f"(d[4]), "+f"(d[5]), "+f"(d[6]), "+f"(d[7]),
      "+f"(d[8]), "+f"(d[9]), "+f"(d[10]), "+f"(d[11]), "+f"(d[12]), "+f"(d[13]), "+f"(d[14]), "+f"(d[15]),
      "+f"(d[16]), "+f"(d[17]), "+f"(d[18]), "+f"(d[19]), "+f"(d[20]), "+f"(d[21]), "+f"(d[22]), "+f"(d[23]),
      "+f"(d[24]), "+f"(d[25]), "+f"(d[26]), "+f"(d[27]), "+f"(d[28]), "+f"(d[29]), "+f"(d[30]), "+f"(d[31]),
      "+f"(d[32]), "+f"(d[33]), "+f"(d[34]), "+f"(d[35]), "+f"(d[36]), "+f"(d[37]), "+f"(d[38]), "+f"(d[39])
    : "l"(da), "l"(db), "r"(scale_d));
}

template <uint32_t HI>
static __device__ __forceinline__ void wgmma_rsl_n64(float (&d)[32], uint32_t a0, uint32_t a1, uint32_t a2, uint32_t a3, uint32_t dlo, int scale_d) {
  asm volatile("{\n.reg .pred p;\n.reg .b64 db;\nsetp.ne.b32 p, %37, 0;\nmov.b64 db, {%36, %38};\n"
    "wgmma.mma_async.sync.aligned.m64n64k16.f32.bf16.bf16 "
    "{%0, %1, %2, %3, %4, %5, %6, %7, %8, %9, %10, %11, %12, %13, %14, %15, %16, %17, %18, %19, %20, %21, %22, %23, %24, %25, %26, %27, %28, %29, %30, %31}, "
    "{%32,%33,%34,%35}, db, p, 1, 1, 0;\n}\n"
    :
      "+f"(d[0]), "+f"(d[1]), "+f"(d[2]), "+f"(d[3]), "+f"(d[4]), "+f"(d[5]), "+f"(d[6]), "+f"(d[7]),
      "+f"(d[8]), "+f"(d[9]), "+f"(d[10]), "+f"(d[11]), "+f"(d[12]), "+f"(d[13]), "+f"(d[14]), "+f"(d[15]),
      "+f"(d[16]), "+f"(d[17]), "+f"(d[18]), "+f"(d[19]), "+f"(d[20]), "+f"(d[21]), "+f"(d[22]), "+f"(d[23]),
      "+f"(d[24]), "+f"(d[25]), "+f"(d[26]), "+f"(d[27]), "+f"(d[28]), "+f"(d[29]), "+f"(d[30]), "+f"(d[31])
    : "r"(a0), "r"(a1), "r"(a2), "r"(a3), "r"(dlo), "r"(scale_d), "n"(HI));
}

template <uint32_t HI>
static __device__ __forceinline__ void wgmma_rsl_n24_tb(float (&d)[12], uint32_t a0, uint32_t a1, uint32_t a2, uint32_t a3, uint32_t dlo, int scale_d) {
  asm volatile("{\n.reg .pred p;\n.reg .b64 db;\nsetp.ne.b32 p, %17, 0;\nmov.b64 db, {%16, %18};\n"
    "wgmma.mma_async.sync.aligned.m64n24k16.f32.bf16.bf16 "
    "{%0, %1, %2, %3, %4, %5, %6, %7, %8, %9, %10, %11}, "
    "{%12,%13,%14,%15}, db, p, 1, 1, 1;\n}\n"
    :
      "+f"(d[0]), "+f"(d[1]), "+f"(d[2]), "+f"(d[3]), "+f"(d[4]), "+f"(d[5]), "+f"(d[6]), "+f"(d[7]),
      "+f"(d[8]), "+f"(d[9]), "+f"(d[10]), "+f"(d[11])
    : "r"(a0), "r"(a1), "r"(a2), "r"(a3), "r"(dlo), "r"(scale_d), "n"(HI));
}

__device__ __forceinline__ void ldsm_x4(uint32_t& r0, uint32_t& r1, uint32_t& r2, uint32_t& r3, uint32_t addr) {
  asm volatile("ldmatrix.sync.aligned.m8n8.x4.shared.b16 {%0,%1,%2,%3}, [%4];"
               : "=r"(r0), "=r"(r1), "=r"(r2), "=r"(r3)
               : "r"(addr)
               : "memory");
}
__device__ __forceinline__ void ldsm_x4_t(uint32_t& r0, uint32_t& r1, uint32_t& r2, uint32_t& r3, uint32_t addr) {
  asm volatile("ldmatrix.sync.aligned.m8n8.x4.trans.shared.b16 {%0,%1,%2,%3}, [%4];"
               : "=r"(r0), "=r"(r1), "=r"(r2), "=r"(r3)
               : "r"(addr)
               : "memory");
}
__device__ __forceinline__ void stsm_x4_t(uint32_t addr, uint32_t r0, uint32_t r1, uint32_t r2, uint32_t r3) {
  asm volatile("stmatrix.sync.aligned.m8n8.x4.trans.shared.b16 [%0], {%1,%2,%3,%4};" ::"r"(addr), "r"(r0), "r"(r1),
               "r"(r2), "r"(r3)
               : "memory");
}
__device__ __forceinline__ uint32_t pack_bf16(float lo, float hi) {
  uint32_t r;
  asm("cvt.rn.bf16x2.f32 %0, %1, %2;" : "=r"(r) : "f"(hi), "f"(lo));
  return r;
}
__device__ __forceinline__ float ex2(float x) {
  float y;
  asm("ex2.approx.ftz.f32 %0, %1;" : "=f"(y) : "f"(x));
  return y;
}
__device__ __forceinline__ uint32_t lds32(uint32_t a) {
  uint32_t v;
  asm volatile("ld.shared.b32 %0, [%1];" : "=r"(v) : "r"(a) : "memory");
  return v;
}
__device__ __forceinline__ void sts32(uint32_t a, uint32_t v) { asm volatile("st.shared.b32 [%0], %1;" ::"r"(a), "r"(v) : "memory"); }
__device__ __forceinline__ void sts64(uint32_t a, uint32_t v0, uint32_t v1) {
  asm volatile("st.shared.v2.b32 [%0], {%1,%2};" ::"r"(a), "r"(v0), "r"(v1) : "memory");
}
__device__ __forceinline__ void sts128(uint32_t a, uint32_t v0, uint32_t v1, uint32_t v2, uint32_t v3) {
  asm volatile("st.shared.v4.b32 [%0], {%1,%2,%3,%4};" ::"r"(a), "r"(v0), "r"(v1), "r"(v2), "r"(v3) : "memory");
}
__device__ __forceinline__ void lds64(uint32_t a, uint32_t& v0, uint32_t& v1) {
  asm volatile("ld.shared.v2.b32 {%0,%1}, [%2];" : "=r"(v0), "=r"(v1) : "r"(a) : "memory");
}
__device__ __forceinline__ void lds128(uint32_t a, uint32_t& v0, uint32_t& v1, uint32_t& v2, uint32_t& v3) {
  asm volatile("ld.shared.v4.b32 {%0,%1,%2,%3}, [%4];" : "=r"(v0), "=r"(v1), "=r"(v2), "=r"(v3) : "r"(a) : "memory");
}
__device__ __forceinline__ uint32_t bmul2(uint32_t a, uint32_t b) {
  uint32_t r;
  asm("mul.rn.bf16x2 %0, %1, %2;" : "=r"(r) : "r"(a), "r"(b));
  return r;
}
__device__ __forceinline__ uint32_t badd2(uint32_t a, uint32_t b) {
  uint32_t r;
  asm("add.rn.bf16x2 %0, %1, %2;" : "=r"(r) : "r"(a), "r"(b));
  return r;
}

struct Params {
  const __nv_bfloat16* x;
  const __nv_bfloat16* wqkv;
  const __nv_bfloat16* wo;
  const __nv_bfloat16* aq;
  const __nv_bfloat16* ak;
  const __nv_bfloat16* av;
  const __nv_bfloat16* shift_k;
  const __nv_bfloat16* ssm_k;
  const __nv_bfloat16* ssm_d;
};

#define PREP_GO_KB 6
#define PF_GO_KB 3
#define PF_H_EARLY 1

template <int ODD, int PART>
__device__ __forceinline__ void qkv_epilogue(const float (&aw)[96], const float (&an)[24], uint32_t sb, int row, int t) {
  const float qs = 0.22360679774997896f * 1.4426950408889634f;
  uint32_t offqk[5], offv[5];
#pragma unroll
  for (int bi = 0; bi < 5; bi++) {
    int u = 2 * bi + t;
    const int cy = u >= 10;
    u -= 10 * cy;
    const uint32_t base = sb + row * 16 + cy * SM_HR;
    offqk[bi] = base + (u >> 2) * 2048 + (u & 3) * 4;
    offv[bi] = base + HR_OWN + (u < 8 ? (3 + (u >> 2)) * 2048 + (u & 3) * 4 : 4096 + 8 + (u - 8) * 4);
  }
#pragma unroll
  for (int j = 0; j < 30; j++) {
    const bool wide = j < 24;
    const int jj = wide ? j : j - 24;
    const int sec = wide ? jj / 8 : jj / 2;
    if ((sec == 0) != (PART == 1)) continue;
    const int c0 = wide ? (ODD ? 16 : 0) + 8 * (jj % 8) : (ODD ? 0 : 64) + 8 * (jj % 2);
    const int a = (c0 / 2) / 10, bi = ((c0 / 2) % 10) / 2;
    const uint32_t ad = (sec == 0 ? offqk[bi] : sec == 1 ? offqk[bi] + HR_OWN : offv[bi]) + a * SM_HR;
    const float v0 = wide ? aw[4 * jj] : an[4 * jj], v1 = wide ? aw[4 * jj + 1] : an[4 * jj + 1];
    const float v2 = wide ? aw[4 * jj + 2] : an[4 * jj + 2], v3 = wide ? aw[4 * jj + 3] : an[4 * jj + 3];
    if (sec == 0) {
      sts32(ad, pack_bf16(v0 * qs, v1 * qs));
      sts32(ad + 128, pack_bf16(v2 * qs, v3 * qs));
    } else {
      sts32(ad, pack_bf16(v0, v1));
      sts32(ad + 128, pack_bf16(v2, v3));
    }
  }
}

__device__ __forceinline__ uint32_t kdesc_lo(uint32_t kv) { return ((kSmemBase + kv) >> 4) | (128u << 16); }
__device__ __forceinline__ uint32_t vdesc_lo(uint32_t kv) { return ((kSmemBase + kv + 4096) >> 4) | (8u << 16); }

__device__ __forceinline__ void issue_qk(float (&s)[32], const uint32_t (&q)[8], uint32_t klo) {
  wgmma_rsl_n64<8>(s, q[0], q[1], q[2], q[3], klo, 0);
  wgmma_rsl_n64<8>(s, q[4], q[5], q[6], q[7], klo + 128, 1);
}
template <int HALF>
__device__ __forceinline__ void issue_pv(float (&o)[12], const uint32_t (&p)[16], uint32_t vlo, int first) {
  wgmma_rsl_n24_tb<128>(o, p[8 * HALF], p[8 * HALF + 1], p[8 * HALF + 2], p[8 * HALF + 3], vlo + 32 * HALF,
                        (HALF == 0 && first) ? 0 : 1);
  wgmma_rsl_n24_tb<128>(o, p[8 * HALF + 4], p[8 * HALF + 5], p[8 * HALF + 6], p[8 * HALF + 7], vlo + 32 * HALF + 16, 1);
}
__device__ __forceinline__ void load_q(uint32_t (&q)[8], uint32_t qaddr, uint32_t zero_addr, int lane) {
  ldsm_x4(q[0], q[1], q[2], q[3], qaddr + (lane >> 4) * 2048);
  ldsm_x4(q[4], q[5], q[6], q[7], lane < 16 ? zero_addr : qaddr + 4096);
}

__device__ __forceinline__ void p_zero(uint32_t& r) { asm volatile("mov.b32 %0, 0;" : "=r"(r)); }

template <int CB>
__device__ __forceinline__ void block_full(const float (&s)[32], uint32_t (&p)[16], float& l0, float& l1) {
  float e[8];
#pragma unroll
  for (int i = 0; i < 8; i++) e[i] = ex2(s[8 * CB + i]);
  l0 += (e[0] + e[1]) + (e[4] + e[5]);
  l1 += (e[2] + e[3]) + (e[6] + e[7]);
#pragma unroll
  for (int r = 0; r < 4; r++) p[4 * CB + r] = pack_bf16(e[2 * r], e[2 * r + 1]);
}
template <int CB>
__device__ __forceinline__ void block_zero(uint32_t (&p)[16]) {
#pragma unroll
  for (int r = 0; r < 4; r++) p_zero(p[4 * CB + r]);
}
template <int KIND, int W>
__device__ __forceinline__ void masked_chunk(const float (&s)[32], uint32_t (&p)[16], float& l0, float& l1, bool pa, bool pb) {
#pragma unroll
  for (int j = 0; j < 8; j++) {
#pragma unroll
    for (int row = 0; row < 2; row++) {
      const int blk = row ? 7 - W : W;
      const int i = 4 * j + 2 * row, pi = 4 * (j >> 1) + 2 * (j & 1) + row;
      float& l = row ? l1 : l0;
      if (j == blk) {
        const float x0 = ex2(s[i]), x1 = ex2(s[i + 1]);
        const float e0 = (pa == (KIND == 2)) ? x0 : 0.f, e1 = (pb == (KIND == 2)) ? x1 : 0.f;
        l += e0 + e1;
        p[pi] = pack_bf16(e0, e1);
      } else if ((j < blk) == (KIND == 2)) {
        const float e0 = ex2(s[i]), e1 = ex2(s[i + 1]);
        l += e0 + e1;
        p[pi] = pack_bf16(e0, e1);
      } else {
        p_zero(p[pi]);
      }
    }
  }
}
template <int KIND>
__device__ __forceinline__ void softmax_masked(const float (&s)[32], uint32_t (&p)[16], float& l0, float& l1, int w, bool pa,
                                               bool pb, bool valid) {
  if (KIND != 2 && !valid) {
    block_zero<0>(p); block_zero<1>(p); block_zero<2>(p); block_zero<3>(p);
  } else if (w == 0) {
    masked_chunk<KIND, 0>(s, p, l0, l1, pa, pb);
  } else if (w == 1) {
    masked_chunk<KIND, 1>(s, p, l0, l1, pa, pb);
  } else if (w == 2) {
    masked_chunk<KIND, 2>(s, p, l0, l1, pa, pb);
  } else {
    masked_chunk<KIND, 3>(s, p, l0, l1, pa, pb);
  }
}
template <int HALF>
__device__ __forceinline__ void softmax_full_half(const float (&s)[32], uint32_t (&p)[16], float& l0, float& l1, bool valid) {
  if (!valid) {
    block_zero<2 * HALF>(p);
    block_zero<2 * HALF + 1>(p);
  } else {
    block_full<2 * HALF>(s, p, l0, l1);
    block_full<2 * HALF + 1>(s, p, l0, l1);
  }
}

__device__ __forceinline__ uint32_t kv_chunk_off(int cc) {
  return (cc < 2 ? HR_R2 : cc < 4 ? HR_R1 : HR_OWN) + (cc & 1) * 1024;
}

__device__ __forceinline__ void attn_tile_safe(float (&o)[12], float& l0, float& l1, uint32_t sb, uint32_t ho, uint32_t zero_addr,
                                               int half, int warp, int lane, int q0) {
  const int g = lane >> 2, t = lane & 3;
  const int r0 = 8 * warp + g, r1 = 56 - 8 * warp + g;
  uint32_t q[8];
  load_q(q, sb + ho + (uint32_t)(64 * half + (((lane >> 3) & 1) ? 56 - 8 * warp : 8 * warp) + (lane & 7)) * 16, zero_addr, lane);
  float s[32];
  uint32_t p[16];
  float m0 = -INFINITY, m1 = -INFINITY;
#pragma unroll 1
  for (int c = 0; c < 5; c++) {
    wg_fence();
    issue_qk(s, q, kdesc_lo(ho + kv_chunk_off(half + c)));
    wg_commit();
    wg_wait<0>();
    fence_regs(s);
#pragma unroll
    for (int j = 0; j < 8; j++) {
#pragma unroll
      for (int e = 0; e < 2; e++) {
        const int rel = 64 * c - 256 + 8 * j + 2 * t + e;
        const bool ok = (q0 + rel >= 0);
        if (ok && rel <= r0 && r0 - rel < 256) m0 = fmaxf(m0, s[4 * j + e]);
        if (ok && rel <= r1 && r1 - rel < 256) m1 = fmaxf(m1, s[4 * j + 2 + e]);
      }
    }
  }
  m0 = fmaxf(m0, __shfl_xor_sync(0xffffffffu, m0, 1));
  m0 = fmaxf(m0, __shfl_xor_sync(0xffffffffu, m0, 2));
  m1 = fmaxf(m1, __shfl_xor_sync(0xffffffffu, m1, 1));
  m1 = fmaxf(m1, __shfl_xor_sync(0xffffffffu, m1, 2));
  l0 = l1 = 0.f;
#pragma unroll 1
  for (int c = 0; c < 5; c++) {
    wg_fence();
    issue_qk(s, q, kdesc_lo(ho + kv_chunk_off(half + c)));
    wg_commit();
    wg_wait<0>();
    fence_regs(s);
#pragma unroll
    for (int j = 0; j < 8; j++) {
      const int rel = 64 * c - 256 + 8 * j + 2 * t;
      const bool ok0 = q0 + rel >= 0, ok1 = q0 + rel + 1 >= 0;
      const float a0 = (ok0 && rel <= r0 && r0 - rel < 256) ? ex2(s[4 * j] - m0) : 0.f;
      const float a1 = (ok1 && rel + 1 <= r0 && r0 - rel - 1 < 256) ? ex2(s[4 * j + 1] - m0) : 0.f;
      const float b0 = (ok0 && rel <= r1 && r1 - rel < 256) ? ex2(s[4 * j + 2] - m1) : 0.f;
      const float b1 = (ok1 && rel + 1 <= r1 && r1 - rel - 1 < 256) ? ex2(s[4 * j + 3] - m1) : 0.f;
      l0 += a0 + a1;
      l1 += b0 + b1;
      p[2 * j] = pack_bf16(a0, a1);
      p[2 * j + 1] = pack_bf16(b0, b1);
    }
    fence_regs(p);
    wg_fence();
    issue_pv<0>(o, p, vdesc_lo(ho + kv_chunk_off(half + c)), c == 0);
    issue_pv<1>(o, p, vdesc_lo(ho + kv_chunk_off(half + c)), 0);
    wg_commit();
    wg_wait<0>();
    fence_regs(o);
  }
}

__device__ __forceinline__ float quad_sum(float v) {
  v += __shfl_xor_sync(0xffffffffu, v, 1);
  v += __shfl_xor_sync(0xffffffffu, v, 2);
  return v;
}
__device__ __forceinline__ bool tile_unsafe(const float (&o)[12], float l0, float l1) {
  float z0 = o[0] * 0.f, z1 = o[1] * 0.f, z2 = o[2] * 0.f;
#pragma unroll
  for (int i = 3; i < 12; i += 3) { z0 = fmaf(o[i], 0.f, z0); z1 = fmaf(o[i + 1], 0.f, z1); z2 = fmaf(o[i + 2], 0.f, z2); }
  const float z = (z0 + z1) + z2;
  return !(l0 >= 8.07e-28f && l0 <= 1.26e30f && l1 >= 8.07e-28f && l1 <= 1.26e30f && z == 0.f);
}
__device__ __forceinline__ float fast_rcp(float x) {
  float y;
  asm("rcp.approx.ftz.f32 %0, %1;" : "=f"(y) : "f"(x));
  return y;
}
__device__ __forceinline__ void write_o(const float (&o)[12], float l0, float l1, uint32_t orow, uint32_t drow, int h, int t) {
  const float i0 = fast_rcp(l0), i1 = fast_rcp(l1);
  const int c1 = 20 * h + 2 * t, c2 = c1 + 8, c0 = c1 + 12;
  const uint32_t a1 = orow + (c1 >> 3) * 1024 + (c1 & 7) * 2;
  const uint32_t a0 = orow + (c0 >> 3) * 1024 + (c0 & 7) * 2;
  sts32(a1, pack_bf16(o[4] * i0, o[5] * i0));
  sts32(a1 + drow, pack_bf16(o[6] * i1, o[7] * i1));
  sts32(a1 + 1024, pack_bf16(o[8] * i0, o[9] * i0));
  sts32(a1 + 1024 + drow, pack_bf16(o[10] * i1, o[11] * i1));
  (void)c2;
  if (t >= 2) {
    sts32(a0, pack_bf16(o[0] * i0, o[1] * i0));
    sts32(a0 + drow, pack_bf16(o[2] * i1, o[3] * i1));
  }
}

#define ATT_STEP(KIND, FIRST_IN_SEQ, sc, sn, pc, PRE, knext, oacc, la, lb, vcur, first, valid) \
  do {                                                                                          \
    if (FIRST_IN_SEQ) wg_wait<0>(); else wg_wait<1>();                                          \
    fence_regs(sc);                                                                             \
    if (KIND == 1) softmax_full_half<0>(sc, pc, la, lb, valid);                                 \
    PRE;                                                                                        \
    wg_fence();                                                                                 \
    issue_qk(sn, q, knext);                                                                     \
    wg_commit();                                                                                \
    if (KIND == 1) softmax_full_half<1>(sc, pc, la, lb, valid);                                 \
    else softmax_masked<(KIND == 1 ? 2 : KIND)>(sc, pc, la, lb, warp, pa, pb, valid);           \
    wg_fence();                                                                                 \
    issue_pv<0>(oacc, pc, vcur, first);                                                         \
    issue_pv<1>(oacc, pc, vcur, 0);                                                             \
    wg_commit();                                                                                \
  } while (0)

__device__ __forceinline__ void consumer_branch(uint32_t sb, uint32_t bars, int wg, int warp, int lane, int rb, int g8,
                                                int rb3, int g3, const CUtensorMap* tm_outh) {
  const int tid128 = warp * 32 + lane;
  const int g = lane >> 2, t = lane & 3;
  {
    float aw[96], an[24];
    const int arow = 64 * wg + 16 * warp + (lane & 15);
    const uint32_t aoff = (uint32_t)arow * 128;
    const uint32_t asw = (uint32_t)(arow & 7);
    uint32_t qa[2][8];
#pragma unroll 1
    for (int kb = 0; kb < 10; kb++) {
      const int s = kb % 3;
      mbar_wait(bars + 8 * (B_FULL + s), (kb / 3) & 1);
      const uint32_t st = sb + s * SM_STAGE;
      const uint32_t so = kSmemBase + s * SM_STAGE;
      const uint32_t wlo = ((so + 16384) >> 4) | ((8192u >> 4) << 16);
      const uint32_t nlo = ((so + 40960) >> 4) | ((2048u >> 4) << 16);
#pragma unroll
      for (int hf = 0; hf < 2; hf++) {
        wg_wait<1>();
        if (hf == 1 && kb > 0 && tid128 == 0) mbar_arrive(bars + 8 * (B_EMPTY + (kb - 1) % 3));
        uint32_t(&q8)[8] = qa[hf];
        const uint32_t c0 = 4 * hf + (lane >> 4);
        ldsm_x4(q8[0], q8[1], q8[2], q8[3], st + aoff + (((c0) ^ asw) << 4));
        ldsm_x4(q8[4], q8[5], q8[6], q8[7], st + aoff + (((c0 + 2) ^ asw) << 4));
        wg_fence();
        wgmma_rsl_n192_tb<0x40000040>(aw, q8[0], q8[1], q8[2], q8[3], wlo + hf * 256, (kb | hf) != 0);
        wgmma_rsl_n48_tb<0xC0000010>(an, q8[0], q8[1], q8[2], q8[3], nlo + hf * 64, (kb | hf) != 0);
        wgmma_rsl_n192_tb<0x40000040>(aw, q8[4], q8[5], q8[6], q8[7], wlo + hf * 256 + 128, 1);
        wgmma_rsl_n48_tb<0xC0000010>(an, q8[4], q8[5], q8[6], q8[7], nlo + hf * 64 + 32, 1);
        wg_commit();
      }
    }
    wg_wait<0>();
    fence_regs(aw);
    fence_regs(an);
    if (tid128 == 0) mbar_arrive(bars + 8 * B_GEMMD);
    named_sync(1, 256);
    const int row = 64 * wg + 16 * warp + g;
    if (g8 & 1) qkv_epilogue<1, 0>(aw, an, sb, row, t); else qkv_epilogue<0, 0>(aw, an, sb, row, t);
    fence_async_smem();
    __syncwarp();
    if (lane == 0) mbar_arrive(bars + 8 * B_EPI);
    if (g8 & 1) qkv_epilogue<1, 1>(aw, an, sb, row, t); else qkv_epilogue<0, 1>(aw, an, sb, row, t);
    {
      const int r = tid128, h0 = 2 * wg;
      sts64(sb + h0 * SM_HR + 4096 + r * 16 + 8, 0u, 0u);
      sts64(sb + (h0 + 1) * SM_HR + 4096 + r * 16 + 8, 0u, 0u);
    }
    fence_async_smem();
    named_sync(1, 256);
  }
  {
    const bool pa = 2 * t <= g, pb = 2 * t + 1 <= g;
    const bool v2 = rb >= 2, v1 = rb >= 1;
    const uint32_t qrow = (uint32_t)((((lane >> 3) & 1) ? 56 - 8 * warp : 8 * warp) + (lane & 7)) * 16;
    const uint32_t orow0 = (uint32_t)(8 * warp + g) * 16, orow1 = (uint32_t)(56 - 16 * warp) * 16;
    const uint32_t zero_addr = sb + SM_ZERO;
    const uint32_t rembar0 = bars + 8 * (B_REM + 2 * wg);
    float s0[32], s1[32], oa[12], ob[12];
    float la0, la1, lb0, lb1;
    uint32_t p0[16], p1[16], q[8];
    const uint32_t qbase = sb + qrow;
    uint32_t ho = 2 * wg * SM_HR;
    load_q(q, qbase + ho, zero_addr, lane);
    wg_fence();
    issue_qk(s0, q, kdesc_lo(ho + HR_OWN));
    wg_commit();

#define ATT_FINISH(HALF, o, l0, l1)                                                                         \
    do {                                                                                                    \
      wg_wait<0>();                                                                                         \
      fence_regs(o);                                                                                        \
      l0 = quad_sum(l0);                                                                                    \
      l1 = quad_sum(l1);                                                                                    \
        \
              \
      if (__any_sync(0xffffffffu, named_sync_or(3 + wg, 128, tile_unsafe(o, l0, l1)))) redo |= 1u << (2 * it + HALF); \
      write_o(o, l0, l1, sb + SM_E + HALF * 10240 + orow0, orow1, 2 * it + wg, t);            \
    } while (0)

    const int nit = 2;
    uint32_t redo = 0;
#pragma unroll 1
    for (int it = 0; it < nit; it++, ho += SM_HR) {
      const uint32_t ko = kdesc_lo(ho + HR_OWN), vo = vdesc_lo(ho + HR_OWN);
      const uint32_t k1 = kdesc_lo(ho + HR_R1), v1d = vdesc_lo(ho + HR_R1);
      const uint32_t k2 = kdesc_lo(ho + HR_R2), v2d = vdesc_lo(ho + HR_R2);
      const uint32_t rembar = rembar0 + 8 * it;
      la0 = la1 = lb0 = lb1 = 0.f;
      ATT_STEP(2, true, s0, s1, p0, load_q(q, qbase + ho + 1024, zero_addr, lane), ko + 64, ob, lb0, lb1, vo, 1, true);
      ATT_STEP(2, false, s1, s0, p1, , ko, oa, la0, la1, vo + 64, 1, true);
      ATT_STEP(1, false, s0, s1, p0, mbar_wait(rembar, 0), k1 + 64, oa, la0, la1, vo, 0, true);
      ATT_STEP(1, false, s1, s0, p1, , k1, oa, la0, la1, v1d + 64, 0, v1);
      ATT_STEP(1, false, s0, s1, p0, , k2 + 64, oa, la0, la1, v1d, 0, v1);
      ATT_STEP(0, false, s1, s0, p1, load_q(q, qbase + ho, zero_addr, lane), k1 + 64, oa, la0, la1, v2d + 64, 0, v2);
      ATT_FINISH(1, oa, la0, la1);
      if (it == 1 && (redo & 8) == 0) {
        fence_async_smem();
        __syncwarp();
        if (lane == 0) mbar_arrive(bars + 8 * (B_OST + 1));
      }
      ATT_STEP(1, true, s0, s1, p0, , k1, ob, lb0, lb1, v1d + 64, 0, v1);
      ATT_STEP(1, false, s1, s0, p1, , k2 + 64, ob, lb0, lb1, v1d, 0, v1);
      ATT_STEP(1, false, s0, s1, p0, , k2, ob, lb0, lb1, v2d + 64, 0, v2);
      const uint32_t hn = it == 0 ? ho + SM_HR : ho;
      ATT_STEP(0, false, s1, s0, p1, load_q(q, qbase + hn, zero_addr, lane), kdesc_lo(hn + HR_OWN), ob, lb0, lb1, v2d, 0, v2);
      ATT_FINISH(0, ob, lb0, lb1);
      if (it == 0 && (redo & 3) == 0) {
        fence_async_smem();
        __syncwarp();
        if (lane == 0) mbar_arrive(bars + 8 * (B_OST + 0));
        if (tid128 == 0) mbar_arrive(bars + 8 * B_H1ST);
      }
    }
    wg_wait<0>();
    fence_regs(s0);
    if (redo) {
#pragma unroll 1
      for (int u = 0; u < 4; u++) {
        if (((redo >> u) & 1) == 0) continue;
        const int it = u >> 1, half = u & 1;
        float os[12], m0, m1;
        attn_tile_safe(os, m0, m1, sb, (2 * wg + it) * SM_HR, zero_addr, half, warp, lane, 128 * rb + 64 * half);
        write_o(os, quad_sum(m0), quad_sum(m1), sb + SM_E + half * 10240 + orow0, orow1, 2 * it + wg, t);
      }
      fence_async_smem();
      __syncwarp();
      if (lane == 0 && (redo & 3)) mbar_arrive(bars + 8 * (B_OST + 0));
      if (tid128 == 0 && (redo & 3)) mbar_arrive(bars + 8 * B_H1ST);
      if (lane == 0 && (redo & 8)) mbar_arrive(bars + 8 * (B_OST + 1));
    }
#undef ATT_FINISH
    if (tid128 == 0) mbar_arrive(bars + 8 * B_ATTD);
    fence_async_smem();
    __syncwarp();
    if (lane == 0) mbar_arrive(bars + 8 * (B_OST + 2));
  }
  {
    float acc[40];
#pragma unroll 1
    for (int i = 0; i < 8; i++) {
      if (i == 0) mbar_wait(bars + 8 * (B_WOF + 0), 0);
      if (i == 4) mbar_wait(bars + 8 * (B_WOF + 1), 0);
      mbar_wait(bars + 8 * (B_OF + 2 * i + wg), 0);
      const uint64_t da = make_desc(sb + o_tile_off(i) + wg * 10240, 1024, 128, 0);
      const uint64_t db = make_desc(sb + wo_part_off(i), 1280, 128, 0);
      wg_fence();
#pragma unroll
      for (int k = 0; k < 5; k++) wgmma_ss_n80_tb(acc, da + k * (2048 >> 4), db + k * (2560 >> 4), (i | k) != 0);
      wg_commit();
      if (i > 0) {
        wg_wait<1>();
        if (i <= 4 && tid128 == 0) mbar_arrive(bars + 8 * (B_OE + 2 * (i - 1) + wg));
      }
    }
    wg_wait<0>();
    fence_regs(acc);
    const uint32_t st = sb + SM_E + wg * 10240;
    const uint32_t ro = st + (uint32_t)(16 * warp + g) * 160 + t * 4;
#pragma unroll
    for (int j = 0; j < 10; j++) {
      sts32(ro + j * 16, pack_bf16(acc[4 * j], acc[4 * j + 1]));
      sts32(ro + 8 * 160 + j * 16, pack_bf16(acc[4 * j + 2], acc[4 * j + 3]));
    }
    fence_async_smem();
    named_sync(3 + wg, 128);
    if (tid128 == 0) {
      tma_store_2d(tm_outh, 640 + 80 * g3, 128 * rb3 + 64 * wg, st);
      bulk_commit();
      bulk_wait_read<0>();
    }
  }
}
template <uint32_t HI>
static __device__ __forceinline__ void wgmma_rsp_n32(float (&d)[64], uint32_t a0, uint32_t a1, uint32_t a2, uint32_t a3, uint32_t dlo, int scale_d) {
  asm volatile("{\n.reg .pred p;\n.reg .b64 db;\nsetp.ne.b32 p, %21, 0;\nmov.b64 db, {%20, %22};\n"
    "wgmma.mma_async.sync.aligned.m64n32k16.f32.bf16.bf16 "
    "{%0, %1, %2, %3, %4, %5, %6, %7, %8, %9, %10, %11, %12, %13, %14, %15}, "
    "{%16,%17,%18,%19}, db, p, 1, 1, 0;\n}\n"
    :
      "+f"(d[0]), "+f"(d[1]), "+f"(d[2]), "+f"(d[3]), "+f"(d[4]), "+f"(d[5]), "+f"(d[6]), "+f"(d[7]),
      "+f"(d[8]), "+f"(d[9]), "+f"(d[10]), "+f"(d[11]), "+f"(d[12]), "+f"(d[13]), "+f"(d[14]), "+f"(d[15])
    : "r"(a0), "r"(a1), "r"(a2), "r"(a3), "r"(dlo), "r"(scale_d), "n"(HI));
}

template <uint32_t HI>
static __device__ __forceinline__ void wgmma_rsp_n64(float (&d)[64], uint32_t a0, uint32_t a1, uint32_t a2, uint32_t a3, uint32_t dlo, int scale_d) {
  asm volatile("{\n.reg .pred p;\n.reg .b64 db;\nsetp.ne.b32 p, %37, 0;\nmov.b64 db, {%36, %38};\n"
    "wgmma.mma_async.sync.aligned.m64n64k16.f32.bf16.bf16 "
    "{%0, %1, %2, %3, %4, %5, %6, %7, %8, %9, %10, %11, %12, %13, %14, %15, %16, %17, %18, %19, %20, %21, %22, %23, %24, %25, %26, %27, %28, %29, %30, %31}, "
    "{%32,%33,%34,%35}, db, p, 1, 1, 0;\n}\n"
    :
      "+f"(d[0]), "+f"(d[1]), "+f"(d[2]), "+f"(d[3]), "+f"(d[4]), "+f"(d[5]), "+f"(d[6]), "+f"(d[7]),
      "+f"(d[8]), "+f"(d[9]), "+f"(d[10]), "+f"(d[11]), "+f"(d[12]), "+f"(d[13]), "+f"(d[14]), "+f"(d[15]),
      "+f"(d[16]), "+f"(d[17]), "+f"(d[18]), "+f"(d[19]), "+f"(d[20]), "+f"(d[21]), "+f"(d[22]), "+f"(d[23]),
      "+f"(d[24]), "+f"(d[25]), "+f"(d[26]), "+f"(d[27]), "+f"(d[28]), "+f"(d[29]), "+f"(d[30]), "+f"(d[31])
    : "r"(a0), "r"(a1), "r"(a2), "r"(a3), "r"(dlo), "r"(scale_d), "n"(HI));
}

template <uint32_t HI>
static __device__ __forceinline__ void wgmma_rsp_n96(float (&d)[64], uint32_t a0, uint32_t a1, uint32_t a2, uint32_t a3, uint32_t dlo, int scale_d) {
  asm volatile("{\n.reg .pred p;\n.reg .b64 db;\nsetp.ne.b32 p, %53, 0;\nmov.b64 db, {%52, %54};\n"
    "wgmma.mma_async.sync.aligned.m64n96k16.f32.bf16.bf16 "
    "{%0, %1, %2, %3, %4, %5, %6, %7, %8, %9, %10, %11, %12, %13, %14, %15, %16, %17, %18, %19, %20, %21, %22, %23, %24, %25, %26, %27, %28, %29, %30, %31, %32, %33, %34, %35, %36, %37, %38, %39, %40, %41, %42, %43, %44, %45, %46, %47}, "
    "{%48,%49,%50,%51}, db, p, 1, 1, 0;\n}\n"
    :
      "+f"(d[0]), "+f"(d[1]), "+f"(d[2]), "+f"(d[3]), "+f"(d[4]), "+f"(d[5]), "+f"(d[6]), "+f"(d[7]),
      "+f"(d[8]), "+f"(d[9]), "+f"(d[10]), "+f"(d[11]), "+f"(d[12]), "+f"(d[13]), "+f"(d[14]), "+f"(d[15]),
      "+f"(d[16]), "+f"(d[17]), "+f"(d[18]), "+f"(d[19]), "+f"(d[20]), "+f"(d[21]), "+f"(d[22]), "+f"(d[23]),
      "+f"(d[24]), "+f"(d[25]), "+f"(d[26]), "+f"(d[27]), "+f"(d[28]), "+f"(d[29]), "+f"(d[30]), "+f"(d[31]),
      "+f"(d[32]), "+f"(d[33]), "+f"(d[34]), "+f"(d[35]), "+f"(d[36]), "+f"(d[37]), "+f"(d[38]), "+f"(d[39]),
      "+f"(d[40]), "+f"(d[41]), "+f"(d[42]), "+f"(d[43]), "+f"(d[44]), "+f"(d[45]), "+f"(d[46]), "+f"(d[47])
    : "r"(a0), "r"(a1), "r"(a2), "r"(a3), "r"(dlo), "r"(scale_d), "n"(HI));
}

template <uint32_t HI>
static __device__ __forceinline__ void wgmma_rsp_n128(float (&d)[64], uint32_t a0, uint32_t a1, uint32_t a2, uint32_t a3, uint32_t dlo, int scale_d) {
  asm volatile("{\n.reg .pred p;\n.reg .b64 db;\nsetp.ne.b32 p, %69, 0;\nmov.b64 db, {%68, %70};\n"
    "wgmma.mma_async.sync.aligned.m64n128k16.f32.bf16.bf16 "
    "{%0, %1, %2, %3, %4, %5, %6, %7, %8, %9, %10, %11, %12, %13, %14, %15, %16, %17, %18, %19, %20, %21, %22, %23, %24, %25, %26, %27, %28, %29, %30, %31, %32, %33, %34, %35, %36, %37, %38, %39, %40, %41, %42, %43, %44, %45, %46, %47, %48, %49, %50, %51, %52, %53, %54, %55, %56, %57, %58, %59, %60, %61, %62, %63}, "
    "{%64,%65,%66,%67}, db, p, 1, 1, 0;\n}\n"
    :
      "+f"(d[0]), "+f"(d[1]), "+f"(d[2]), "+f"(d[3]), "+f"(d[4]), "+f"(d[5]), "+f"(d[6]), "+f"(d[7]),
      "+f"(d[8]), "+f"(d[9]), "+f"(d[10]), "+f"(d[11]), "+f"(d[12]), "+f"(d[13]), "+f"(d[14]), "+f"(d[15]),
      "+f"(d[16]), "+f"(d[17]), "+f"(d[18]), "+f"(d[19]), "+f"(d[20]), "+f"(d[21]), "+f"(d[22]), "+f"(d[23]),
      "+f"(d[24]), "+f"(d[25]), "+f"(d[26]), "+f"(d[27]), "+f"(d[28]), "+f"(d[29]), "+f"(d[30]), "+f"(d[31]),
      "+f"(d[32]), "+f"(d[33]), "+f"(d[34]), "+f"(d[35]), "+f"(d[36]), "+f"(d[37]), "+f"(d[38]), "+f"(d[39]),
      "+f"(d[40]), "+f"(d[41]), "+f"(d[42]), "+f"(d[43]), "+f"(d[44]), "+f"(d[45]), "+f"(d[46]), "+f"(d[47]),
      "+f"(d[48]), "+f"(d[49]), "+f"(d[50]), "+f"(d[51]), "+f"(d[52]), "+f"(d[53]), "+f"(d[54]), "+f"(d[55]),
      "+f"(d[56]), "+f"(d[57]), "+f"(d[58]), "+f"(d[59]), "+f"(d[60]), "+f"(d[61]), "+f"(d[62]), "+f"(d[63])
    : "r"(a0), "r"(a1), "r"(a2), "r"(a3), "r"(dlo), "r"(scale_d), "n"(HI));
}

template <int N>
__device__ __forceinline__ void conv_wg(float (&d)[64], const uint32_t (&a)[4], uint32_t lo, int sc);
template <>
__device__ __forceinline__ void conv_wg<32>(float (&d)[64], const uint32_t (&a)[4], uint32_t lo, int sc) {
  wgmma_rsp_n32<8>(d, a[0], a[1], a[2], a[3], lo, sc);
}
template <>
__device__ __forceinline__ void conv_wg<64>(float (&d)[64], const uint32_t (&a)[4], uint32_t lo, int sc) {
  wgmma_rsp_n64<8>(d, a[0], a[1], a[2], a[3], lo, sc);
}
template <>
__device__ __forceinline__ void conv_wg<96>(float (&d)[64], const uint32_t (&a)[4], uint32_t lo, int sc) {
  wgmma_rsp_n96<8>(d, a[0], a[1], a[2], a[3], lo, sc);
}
template <>
__device__ __forceinline__ void conv_wg<128>(float (&d)[64], const uint32_t (&a)[4], uint32_t lo, int sc) {
  wgmma_rsp_n128<8>(d, a[0], a[1], a[2], a[3], lo, sc);
}

#define Q_LOAD_CH 3
#define CONV_RING 7
#define CONV_AHEAD 3
constexpr int kRing = CONV_RING, kAhead = CONV_AHEAD;
template <int J>
__device__ __forceinline__ void conv_load_a(uint32_t (&a)[4], uint32_t ha) {
  constexpr int S = 32 * (J / 8) + J % 8;
  a[0] = lds32(ha + 32 * S);
  a[1] = lds32(ha + 32 * S + 256);
  a[2] = lds32(ha + 32 * S + 16);
  asm volatile("ld.volatile.shared.b32 %0, [%1];" : "=r"(a[3]) : "r"(ha + 32 * S + 272) : "memory");
}
template <int J>
__device__ __forceinline__ void conv_preload(uint32_t (&a)[kRing][4], uint32_t ha) {
  if constexpr (J < kAhead) {
    conv_load_a<J>(a[J], ha);
    conv_preload<J + 1>(a, ha);
  }
}
template <int HI>
__device__ __forceinline__ void conv_fold(const float (&d)[64], float (&keep)[16], uint32_t rw) {
#pragma unroll
  for (int j = 0; j < 8; j++) {
    const int ks = HI ? 10 + j : j, ss = HI ? 2 + j : 8 + j;
#pragma unroll
    for (int e = 0; e < 2; e++)
      keep[2 * j + e] = (ks < 16 ? d[4 * ks + e] : 0.f) + (ks + 1 < 16 ? d[4 * (ks + 1) + 2 + e] : 0.f);
    sts64(rw + j * 256, __float_as_uint(d[4 * ss] + (ss + 1 < 16 ? d[4 * (ss + 1) + 2] : 0.f)),
          __float_as_uint(d[4 * ss + 1] + (ss + 1 < 16 ? d[4 * (ss + 1) + 3] : 0.f)));
  }
}
__device__ __forceinline__ void conv_finish(const float (&keep)[16], uint32_t rr, uint32_t sb, int warp, int lane, bool store,
                                            uint8_t* zdst) {
  uint32_t zp[8];
#pragma unroll
  for (int j = 0; j < 8; j++) {
    uint32_t v0, v1;
    lds64(rr + j * 256, v0, v1);
    zp[j] = pack_bf16(keep[2 * j] + __uint_as_float(v0), keep[2 * j + 1] + __uint_as_float(v1));
  }
#pragma unroll
  for (int m = 0; m < 2; m++) {
    const int c = 8 * (8 * (warp >> 1) + 4 * m + (lane >> 3)) + (lane & 7);
    stsm_x4_t(sb + SM_CZ + (uint32_t)(127 - c) * 32 + (warp & 1) * 16, zp[4 * m], zp[4 * m + 1], zp[4 * m + 2], zp[4 * m + 3]);
  }
  fence_async_smem();
  named_sync(2, 128);
  if (store) {
    bulk_store(zdst, sb + SM_CZ, 4096);
    bulk_commit();
  }
}
struct ConvCtx {
  uint32_t sb, ha, xlo, rr, hstore;
  int warp, lane;
  bool store;
  uint8_t* zdst;
  const __nv_bfloat16* hnext;
  int tid;
};
struct Taps {
  uint4 v0, v1;
  uint32_t n0, n1;
};
__device__ __forceinline__ void load_taps(Taps& tp, const __nv_bfloat16* h, bool last_thread) {
  asm volatile("ld.volatile.global.v4.b32 {%0,%1,%2,%3}, [%4];"
               : "=r"(tp.v0.x), "=r"(tp.v0.y), "=r"(tp.v0.z), "=r"(tp.v0.w) : "l"(h) : "memory");
  asm volatile("ld.volatile.global.v4.b32 {%0,%1,%2,%3}, [%4];"
               : "=r"(tp.v1.x), "=r"(tp.v1.y), "=r"(tp.v1.z), "=r"(tp.v1.w) : "l"(h + 1024) : "memory");
  uint16_t a, c;
  asm volatile("ld.volatile.global.b16 %0, [%1];" : "=h"(a) : "l"(h + 8) : "memory");
  asm volatile("ld.volatile.global.b16 %0, [%1];" : "=h"(c) : "l"(h + (last_thread ? 0 : 1032)) : "memory");
  tp.n0 = a;
  tp.n1 = c;
}
__device__ __forceinline__ void store_taps(const Taps& tp, uint32_t hb, int tid) {
  sts128(hb + 32 + 16 * tid, tp.v0.x, tp.v0.y, tp.v0.z, tp.v0.w);
  sts128(hb + 32 + 16 * (tid + 128), tp.v1.x, tp.v1.y, tp.v1.z, tp.v1.w);
  sts128(hb + 4160 + 16 * (tid + 2), __byte_perm(tp.v0.x, tp.v0.y, 0x5432), __byte_perm(tp.v0.y, tp.v0.z, 0x5432),
         __byte_perm(tp.v0.z, tp.v0.w, 0x5432), __byte_perm(tp.v0.w, tp.n0, 0x5432));
  sts128(hb + 4160 + 16 * (tid + 130), __byte_perm(tp.v1.x, tp.v1.y, 0x5432), __byte_perm(tp.v1.y, tp.v1.z, 0x5432),
         __byte_perm(tp.v1.z, tp.v1.w, 0x5432), __byte_perm(tp.v1.w, tid == 127 ? 0u : tp.n1, 0x5432));
  if (tid == 0) sts128(hb + 4160 + 16, 0u, 0u, 0u, tp.v0.x << 16);
}
template <int J>
__device__ __forceinline__ void conv_steps(float (&d)[64], uint32_t (&a)[kRing][4], const float (&keep)[16], Taps& tp,
                                           const ConvCtx& c) {
  if constexpr (J < 32) {
    if constexpr (J + kAhead < 32) {
      if constexpr (J + kAhead >= kRing) wg_wait<kRing - kAhead - 1>();
      conv_load_a<J + kAhead>(a[(J + kAhead) % kRing], c.ha);
    }
    wg_fence();
    conv_wg<128 - 32 * (J / 8)>(d, a[J % kRing], c.xlo + 32 * (J / 8) + J % 8, 1);
    wg_commit();
    if constexpr (J == 3) conv_finish(keep, c.rr, c.sb, c.warp, c.lane, c.store, c.zdst);
    if constexpr (J == 4) load_taps(tp, c.hnext, c.tid == 127);
    if constexpr (J == 26) store_taps(tp, c.hstore, c.tid);
    conv_steps<J + 1>(d, a, keep, tp, c);
  }
}

__device__ __forceinline__ void branch_a(uint32_t sb, uint32_t bars, int warp, int lane, int rb, int g8, const Params& p,
                                         const CUtensorMap* tm_k, const CUtensorMap* tm_v, const CUtensorMap* tm_q,
                                         const CUtensorMap* tm_xt, const CUtensorMap* tm_z, const CUtensorMap* tm_out) {
  const int tid = warp * 32 + lane;
  unsigned ticket = 0;
  const int ch0 = 80 * g8 + 5 * rb;
  if (tid == 0) {
    ticket = atomicAdd(&g_ticket[32], 1u);
    mbar_wait(bars + 8 * B_GO, 0);
    mbar_expect_tx(bars + 8 * B_KV, 21120 + 20480);
    tma_load_2d(sb + SM_C, tm_k, 80 * g8, 128 * rb - 4, bars + 8 * B_KV);
    tma_load_2d(sb + SM_C + 21120, tm_v, 80 * g8, 128 * rb, bars + 8 * B_KV);
  }
  uint4 wall[3];
#pragma unroll
  for (int r = 0; r < 3; r++) {
    const int it = min(tid + 128 * r, 319);
    wall[r] = *reinterpret_cast<const uint4*>(p.shift_k + (size_t)(80 * g8 + 2 * (it % 40)) * 4);
  }
  mbar_wait(bars + 8 * B_KV, 0);
#pragma unroll
  for (int r = 0; r < 3; r++) {
    const int it = tid + 128 * r;
    if (it >= 320) break;
    const int pr = it % 40, bq = it / 40;
    const uint4 wv = wall[r];
    const uint32_t w0 = __byte_perm(wv.x, wv.z, 0x5410), w1 = __byte_perm(wv.x, wv.z, 0x7632);
    const uint32_t w2 = __byte_perm(wv.y, wv.w, 0x5410), w3 = __byte_perm(wv.y, wv.w, 0x7632);
    const uint32_t ka = sb + SM_C + (uint32_t)(16 * bq + 1) * 160 + pr * 4;
    const uint32_t va = sb + SM_C + 21120 + (uint32_t)(16 * bq) * 160 + pr * 4;
    uint32_t kr[19], kv[16];
#pragma unroll
    for (int i = 0; i < 19; i++) kr[i] = lds32(ka + i * 160);
#pragma unroll
    for (int i = 0; i < 16; i++) {
      uint32_t a = bmul2(kr[i], w3);
      a = badd2(a, bmul2(kr[i + 1], w2));
      a = badd2(a, bmul2(kr[i + 2], w1));
      a = badd2(a, bmul2(kr[i + 3], w0));
      kv[i] = bmul2(a, lds32(va + i * 160));
    }
    const uint32_t row0 = 4 * pr, ck = 7 - bq;
    const uint32_t st0 = sb + SM_CSTG + row0 * 128;
    sts128(st0 + ((ck ^ (row0 & 7)) << 4), __byte_perm(kv[15], kv[14], 0x5410), __byte_perm(kv[13], kv[12], 0x5410),
           __byte_perm(kv[11], kv[10], 0x5410), __byte_perm(kv[9], kv[8], 0x5410));
    sts128(st0 + 128 + ((ck ^ ((row0 + 1) & 7)) << 4), __byte_perm(kv[7], kv[6], 0x5410), __byte_perm(kv[5], kv[4], 0x5410),
           __byte_perm(kv[3], kv[2], 0x5410), __byte_perm(kv[1], kv[0], 0x5410));
    sts128(st0 + 256 + ((ck ^ ((row0 + 2) & 7)) << 4), __byte_perm(kv[15], kv[14], 0x7632), __byte_perm(kv[13], kv[12], 0x7632),
           __byte_perm(kv[11], kv[10], 0x7632), __byte_perm(kv[9], kv[8], 0x7632));
    sts128(st0 + 384 + ((ck ^ ((row0 + 3) & 7)) << 4), __byte_perm(kv[7], kv[6], 0x7632), __byte_perm(kv[5], kv[4], 0x7632),
           __byte_perm(kv[3], kv[2], 0x7632), __byte_perm(kv[1], kv[0], 0x7632));
  }
  fence_async_smem();
  named_sync(2, 128);
  if (tid == 0) {
    tma_store_3d(tm_xt, (120 - 8 * rb) * 8, 0, 80 * g8, sb + SM_CSTG);
    bulk_commit();
  }
  Taps tp;
  load_taps(tp, p.ssm_k + (size_t)ch0 * kS + 8 * tid, tid == 127);
  if (tid == 0) {
    bulk_wait<0>();
    fence_release();
    red_relaxed(&g_cnt[(CNT_PREP + g8) * 32], 1);
  }
  named_sync(2, 128);
  store_taps(tp, sb + SM_CH, tid);
  if (tid < 6) sts128(sb + SM_CH + (tid / 3) * 8320 + (tid % 3 == 2 ? 4160 : 16 * (tid % 3)), 0u, 0u, 0u, 0u);
  if (tid < 32) sts128(sb + SM_CX + (tid >> 4) * 4352 + ((tid >> 3) & 1) * 2176 + 2048 + (tid & 7) * 16, 0u, 0u, 0u, 0u);
  const unsigned epoch1 = ticket / kNumCta + 1;
  if (tid == 0) {
    wait_counter(&g_cnt[(CNT_PREP + g8) * 32], epoch1 * 16);
    fence_async_global();
    fence_async_smem();
#pragma unroll
    for (int i = 0; i < 2; i++) {
      mbar_expect_tx(bars + 8 * (B_X + i), 4096);
      bulk_load(sb + SM_CX + i * 4352, g_xt + (size_t)(ch0 + i) * 4096, 2048, bars + 8 * (B_X + i));
      bulk_load(sb + SM_CX + i * 4352 + 2176, g_xt + (size_t)(ch0 + i) * 4096 + 2048, 2048, bars + 8 * (B_X + i));
    }
  }
  fence_async_smem();
  named_sync(2, 128);

  const int g = lane >> 2, t = lane & 3;
  {
    const uint32_t ha0 = sb + SM_CH + 512 * (warp >> 1) + 16 * (warp & 1) +
                         ((g & 1) ? (uint32_t)(4 * ((g + 1) / 2 + t)) : (uint32_t)(4160 + 4 * (g / 2 + t)));
    const uint32_t rw = sb + SM_CR + warp * 2048 + lane * 8;
    const uint32_t rr = sb + SM_CR + (warp ^ 2) * 2048 + lane * 8;
    const uint32_t dall = (warp < 2 && lane < 5) ? (uint32_t) * reinterpret_cast<const uint16_t*>(p.ssm_d + ch0 + lane) : 0u;
    float keep[16];
#pragma unroll
    for (int i = 0; i < 16; i++) keep[i] = 0.f;
    const int nch = 5;
#pragma unroll 1
    for (int i = 0; i < nch; i++) {
      const uint32_t xa = sb + SM_CX + (i & 1) * 4352;
      const uint32_t xlo = ((kSmemBase + (SM_CX + (i & 1) * 4352)) >> 4) | ((2176u >> 4) << 16);
      const uint32_t ha = ha0 + (i & 1) * 8320;
      const uint32_t dv = __shfl_sync(0xffffffffu, dall, i);
      float d[64];
      uint32_t a[kRing][4];
      conv_preload<0>(a, ha);
      uint32_t df[4];
      const uint32_t dm = (2 * t == 7 - g) ? dv : ((2 * t + 1 == 7 - g) ? (dv << 16) : 0u);
      df[0] = (warp & 1) ? dm : 0u;
      df[2] = (warp & 1) ? 0u : dm;
      df[1] = df[3] = 0u;
      mbar_wait(bars + 8 * (B_X + (i & 1)), (i >> 1) & 1);
      wg_fence();
      conv_wg<128>(d, df, xlo, 0);
      wg_commit();
      {
        ConvCtx c{sb, ha, xlo, rr, sb + SM_CH + ((i + 1) & 1) * 8320, warp, lane, tid == 0 && i > 0,
                  g_zt + (size_t)(ch0 + i - 1) * 4096, p.ssm_k + (size_t)(ch0 + (i < 4 ? i + 1 : 4)) * kS + 8 * tid, tid};
        conv_steps<0>(d, a, keep, tp, c);
      }
      wg_wait<0>();
      fence_regs(d);
      if (warp >> 1) conv_fold<1>(d, keep, rw); else conv_fold<0>(d, keep, rw);
      if (tid == 0) bulk_wait_read<0>();
      named_sync(2, 128);
      if (tid == 0 && i == Q_LOAD_CH) {
        mbar_expect_tx(bars + 8 * B_FIN, 20480 + 20480);
        tma_load_2d(sb + SM_CQ, tm_q, 80 * g8, 128 * rb, bars + 8 * B_FIN);
      }
      if (tid == 0 && i < 3) {
        mbar_expect_tx(bars + 8 * (B_X + (i & 1)), 4096);
        bulk_load(xa, g_xt + (size_t)(ch0 + i + 2) * 4096, 2048, bars + 8 * (B_X + (i & 1)));
        bulk_load(xa + 2176, g_xt + (size_t)(ch0 + i + 2) * 4096 + 2048, 2048, bars + 8 * (B_X + (i & 1)));
      }
    }
    conv_finish(keep, rr, sb, warp, lane, tid == 0, g_zt + (size_t)(ch0 + 4) * 4096);
    if (tid == 0) {
      bulk_wait<0>();
      fence_release();
      red_relaxed(&g_cnt[(CNT_CONV + g8) * 32], 1);
    }
    named_sync(2, 128);
  }
  if (tid == 0) {
    wait_counter(&g_cnt[(CNT_CONV + g8) * 32], epoch1 * 16);
    fence_async_global();
    fence_async_smem();
    tma_load_2d(sb + SM_C, tm_z, 128 * rb, 80 * g8, bars + 8 * B_FIN);
    tma_load_2d(sb + SM_C + 10240, tm_z, 128 * rb + 64, 80 * g8, bars + 8 * B_FIN);
  }
  mbar_wait(bars + 8 * B_FIN, 0);
  {
    const int sc = 4 * warp + (lane >> 3);
    const uint32_t zb = sb + SM_C + (sc >> 3) * 10240 + (lane & 7) * 128 + (((sc & 7) ^ (lane & 7)) << 4);
    const uint32_t qb = sb + SM_CQ + (uint32_t)(32 * warp + g) * 160 + t * 4;
    uint32_t z[10][4];
#pragma unroll
    for (int c = 0; c < 10; c++) ldsm_x4_t(z[c][0], z[c][1], z[c][2], z[c][3], zb + c * 1024);
#pragma unroll
    for (int m = 0; m < 4; m++) {
      uint32_t qv[10];
#pragma unroll
      for (int c = 0; c < 10; c++) qv[c] = lds32(qb + m * 8 * 160 + c * 16);
#pragma unroll
      for (int c = 0; c < 10; c++) sts32(qb + m * 8 * 160 + c * 16, bmul2(qv[c], z[c][m]));
    }
    fence_async_smem();
    __syncwarp();
    if (lane == 0) {
      tma_store_2d(tm_out, 80 * g8, 128 * rb + 32 * warp, sb + SM_CQ + warp * 32 * 160);
      bulk_commit();
      bulk_wait_read<0>();
    }
  }
}
__device__ __forceinline__ void o_loader(uint32_t sb, uint32_t bars, int lane, int rb, int g8, int rb3, int hf,
                                         unsigned epoch1) {
  const int part = (lane & 1) ? (hf ? 1 : 2) : 0;
  const unsigned* flag = &g_cnt[(CNT_ATT + (lane < 16 ? (rb3 * 8 + (lane >> 1)) * 3 + part : (rb * 8 + g8) * 3 + 2)) * 32];
  int i = 0;
  uint32_t spins = 0;
  if (lane == 0) mbar_wait(bars + 8 * B_ATTD, 0);
  __syncwarp();
  while (i < 8) {
    const bool ok = lane > 16 || (int)(ld_acquire(flag) - epoch1) >= 0;
    const uint32_t m = __ballot_sync(0xffffffffu, ok);
    if (lane == 0) fence_async_global();
    while (i < 8) {
      const int j = 2 * (i & 3), sec = i >> 2;
      const uint32_t need = (1u << (2 * j + sec)) | (1u << (2 * j + 2 + sec)) | ((i == 2 || i == 5) ? 1u << 16 : 0u);
      if ((m & need) != need) break;
      if (lane == 0) {
        if (i == 7) { mbar_wait(bars + 8 * (B_OE + 2), 0); mbar_wait(bars + 8 * (B_OE + 3), 0); }
        else if (i >= 3) mbar_wait(bars + 8 * (B_OE + 2 * (i - 3) + hf), 0);
        const uint32_t fb = bars + 8 * (B_OF + 2 * i + hf);
        mbar_expect_tx(fb, 10240);
        bulk_load(sb + o_tile_off(i) + hf * 10240, g_o + ((size_t)((rb3 * 2 + hf) * 2 + sec) * 8 + j) * 5120, 10240, fb);
      }
      __syncwarp();
      i++;
    }
    if (++spins > (1u << 20)) wait_timeout_trap();
  }
}

__device__ __forceinline__ void producer(uint32_t sb, uint32_t bars, int lane, int rb, int g8, int rb3, int g3,
                                         const CUtensorMap* tm_x, const CUtensorMap* tm_ww, const CUtensorMap* tm_wn) {
  unsigned ticket = 0;
  if (lane == 0) {
    const int cw = 80 * g8 + ((g8 & 1) ? 16 : 0), cn = 80 * g8 + ((g8 & 1) ? 0 : 64);
#pragma unroll 1
    for (int kb = 0; kb < 10; kb++) {
      const int s = kb % 3;
      if (kb >= 3) mbar_wait(bars + 8 * (B_EMPTY + s), ((kb / 3) - 1) & 1);
      const uint32_t st = sb + s * SM_STAGE, fb = bars + 8 * (B_FULL + s);
      mbar_expect_tx(fb, SM_STAGE);
      tma_load_2d(st, tm_x, kb * 64, rb * 128, fb);
      tma_load_3d(st + 16384, tm_ww, cw, kb * 64, 0, fb);
      tma_load_3d(st + 40960, tm_wn, cn, kb * 64, 0, fb);
      if (kb == 2) ticket = atomicAdd(&g_ticket[0], 1u);
      if (kb == PF_GO_KB) mbar_arrive(bars + 8 * B_GO0);
      if (kb == PREP_GO_KB) mbar_arrive(bars + 8 * B_GO);
    }
    mbar_wait(bars + 8 * B_GEMMD, 0);
  }
  const unsigned epoch1 = __shfl_sync(0xffffffffu, ticket, 0) / kNumCta + 1;
  {
    const int rb1 = rb >= 1 ? rb - 1 : 0, rb2 = rb >= 2 ? rb - 2 : 0;
    const int li = (lane >> 1) & 3, lh = ((li & 1) << 1) | (li >> 1);
    const unsigned* flag = &g_cnt[(CNT_KV + (((lane & 1) ? rb1 : rb2) * 8 + g8) * 4 + lh) * 32];
    uint32_t issued = 0, spins = 0;
    while (issued != 0xF) {
      const bool ok = lane >= 8 || (int)(ld_acquire(flag) - epoch1) >= 0;
      const uint32_t m = __ballot_sync(0xffffffffu, ok);
      if (lane == 0) {
#pragma unroll 1
        for (int i = 0; i < 4; i++) {
          if (!((issued >> i) & 1) && ((m >> (2 * i)) & 3) == 3) {
            const int h = ((i & 1) << 1) | (i >> 1);
            fence_async_global();
            const uint32_t hr = sb + h * SM_HR, fb = bars + 8 * (B_REM + h);
            mbar_expect_tx(fb, 20480);
            bulk_load(hr + HR_R2, g_kv + ((size_t)(4 * g8 + h) * 16 + rb2) * 10240, 10240, fb);
            bulk_load(hr + HR_R1, g_kv + ((size_t)(4 * g8 + h) * 16 + rb1) * 10240, 10240, fb);
          }
        }
      }
#pragma unroll
      for (int i = 0; i < 4; i++)
        if (((m >> (2 * i)) & 3) == 3) issued |= 1u << i;
      if (++spins > (1u << 20)) wait_timeout_trap();
    }
  }
  const uint8_t* wo = g_wo + (size_t)g3 * 102400;
  if (lane == 0) {
    wait_counter(&g_cnt[CNT_WO * 32], epoch1 * 80);
    fence_async_global();
    mbar_wait(bars + 8 * B_H1ST, 0);
    mbar_expect_tx(bars + 8 * (B_WOF + 0), 4 * 12800);
#pragma unroll 1
    for (int i = 0; i < 4; i++) bulk_load(sb + wo_part_off(i), wo + i * 12800, 12800, bars + 8 * (B_WOF + 0));
    mbar_wait(bars + 8 * B_ATTD, 0);
    mbar_expect_tx(bars + 8 * (B_WOF + 1), 4 * 12800);
#pragma unroll 1
    for (int i = 4; i < 8; i++) bulk_load(sb + wo_part_off(i), wo + i * 12800, 12800, bars + 8 * (B_WOF + 1));
  }
  __syncwarp();
  o_loader(sb, bars, lane, rb, g8, rb3, 1, epoch1);
}

__device__ __forceinline__ void store_agent(uint32_t sb, uint32_t bars, int lane, int rb, int g8) {
  mbar_wait(bars + 8 * B_EPI, 0);
  if (lane == 0) {
    unsigned* kvf = &g_cnt[(CNT_KV + (rb * 8 + g8) * 4) * 32];
#pragma unroll 1
    for (int sec = 0; sec < 2; sec++) {
      bulk_store(g_kv + ((size_t)(4 * g8 + sec) * 16 + rb) * 10240, sb + sec * SM_HR + HR_OWN, 10240);
      bulk_store(g_kv + ((size_t)(4 * g8 + 2 + sec) * 16 + rb) * 10240, sb + (2 + sec) * SM_HR + HR_OWN, 10240);
      bulk_commit();
      bulk_wait<0>();
      fence_release();
      red_relaxed(kvf + sec * 32, 1);
      red_relaxed(kvf + (2 + sec) * 32, 1);
    }
  }
  __syncwarp();
  uint8_t* obase = g_o + ((size_t)rb * 4 * 8 + g8) * 5120;
  unsigned* oflag = &g_cnt[(CNT_ATT + (rb * 8 + g8) * 3) * 32];
  mbar_wait(bars + 8 * (B_OST + 0), 0);
  if (lane == 0) {
    bulk_store(obase, sb + SM_E, 5120);
    bulk_store(obase + 2 * 8 * 5120, sb + SM_E + 10240, 5120);
    bulk_commit();
    bulk_wait<0>();
    fence_release();
    red_relaxed(oflag, 1);
  }
  __syncwarp();
  mbar_wait(bars + 8 * (B_OST + 1), 0);
  warp_copy_out<5120>(obase + 3 * 8 * 5120, sb + SM_E + 10240 + 5120, lane);
  __syncwarp();
  if (lane == 0) {
    fence_release();
    red_relaxed(oflag + 32, 1);
  }
  __syncwarp();
  mbar_wait(bars + 8 * (B_OST + 2), 0);
  warp_copy_out<5120>(obase + 1 * 8 * 5120, sb + SM_E + 5120, lane);
  __syncwarp();
  if (lane == 0) {
    fence_release();
    red_relaxed(oflag + 64, 1);
  }
}

__device__ __forceinline__ void prefetch_agent(uint32_t bars, int cta, int rb, int g8, const Params& p,
                                               const CUtensorMap* tm_x, const CUtensorMap* tm_ww,
                                               const CUtensorMap* tm_wn, const CUtensorMap* tm_k, const CUtensorMap* tm_v) {
  mbar_wait(bars + 8 * (B_FULL + 0), 0);
  if (g8 < 7) tma_prefetch_2d(tm_x, (3 + g8) * 64, rb * 128);
  if (rb < 7) {
    tma_prefetch_3d(tm_ww, 80 * g8 + ((g8 & 1) ? 16 : 0), (3 + rb) * 64, 0);
    tma_prefetch_3d(tm_wn, 80 * g8 + ((g8 & 1) ? 0 : 64), (3 + rb) * 64, 0);
  }
  mbar_wait(bars + 8 * B_GO0, 0);
  tma_prefetch_2d(tm_k, 80 * g8, 128 * rb - 4);
  tma_prefetch_2d(tm_v, 80 * g8, 128 * rb);
  mbar_wait(bars + 8 * B_GO, 0);
#pragma unroll 1
  for (int i = 0; i < PF_H_EARLY; i++) l2_prefetch(p.ssm_k + (size_t)(80 * g8 + 5 * rb + i) * kS, 4096);
  mbar_wait(bars + 8 * B_GEMMD, 0);
#pragma unroll 1
  for (int i = PF_H_EARLY; i < 5; i++) l2_prefetch(p.ssm_k + (size_t)(80 * g8 + 5 * rb + i) * kS, 4096);
  l2_prefetch((const uint8_t*)p.aq + (size_t)cta * 20480, 20480);
}

__device__ __forceinline__ void aux_warp(uint32_t sb, int lane, int cta, const Params& p) {
  if (cta < 80) {
    const int r = lane & 7, qs = lane >> 3;
    const int pi = cta / 10, q = cta % 10;
    const int col = 8 * (q % 5 + 5 * (pi >> 2)) + r, pos = col / 20;
    const int krow = 80 * (2 * (pi & 3) + (q >= 5)) + 20 * ((pos >> 1) | ((pos & 1) << 1)) + col % 20;
    const uint8_t* src = (const uint8_t*)p.wo + (size_t)krow * 1280 + qs * 16;
    const uint32_t dst = sb + SM_E + qs * 128 + r * 16;
#pragma unroll 1
    for (int q0 = 0; q0 < 80; q0 += 20) {
      uint4 v[5];
#pragma unroll
      for (int i = 0; i < 5; i++) v[i] = ldg_stream(src + (q0 + 4 * i) * 16);
#pragma unroll
      for (int i = 0; i < 5; i++) sts128(dst + (q0 + 4 * i) * 128, v[i].x, v[i].y, v[i].z, v[i].w);
    }
    fence_async_smem();
    __syncwarp();
    if (lane == 0) {
#pragma unroll 1
      for (int gg = 0; gg < 8; gg++) bulk_store(g_wo + (size_t)gg * 102400 + cta * 1280, sb + SM_E + gg * 1280, 1280);
      bulk_commit();
      bulk_wait<0>();
      fence_release();
      red_relaxed(&g_cnt[CNT_WO * 32], 1);
    }
  }
}

__global__ void __launch_bounds__(kThreads, 1)
h3_swa_fused_kernel(const __grid_constant__ CUtensorMap tm_x, const __grid_constant__ CUtensorMap tm_ww,
                    const __grid_constant__ CUtensorMap tm_wn, const __grid_constant__ CUtensorMap tm_k,
                    const __grid_constant__ CUtensorMap tm_v, const __grid_constant__ CUtensorMap tm_q,
                    const __grid_constant__ CUtensorMap tm_xt, const __grid_constant__ CUtensorMap tm_z,
                    const __grid_constant__ CUtensorMap tm_out, const __grid_constant__ CUtensorMap tm_outh,
                    const Params p) {
  extern __shared__ __align__(1024) uint8_t smem[];
  const uint32_t sb = smem_u32(smem);
  const uint32_t bars = sb + SM_BAR;
  if ((sb & 0xFFFFFFu) != kSmemBase) __trap();
  const int warp = __shfl_sync(0xffffffffu, threadIdx.x >> 5, 0), lane = threadIdx.x & 31;
  const int pair = blockIdx.x >> 1, odd = blockIdx.x & 1;
  const int g8 = pair & 7, rb = 2 * (pair >> 3) + odd;
  const int rb3 = pair >> 2, g3 = 2 * (pair & 3) + odd;

  if (threadIdx.x == 0) {
    for (int i = 0; i < 3; i++) {
      mbar_init(bars + 8 * (B_FULL + i), 1);
      mbar_init(bars + 8 * (B_EMPTY + i), 2);
    }
    for (int i = 0; i < 16; i++) mbar_init(bars + 8 * (B_OF + i), 1);
    for (int i = 0; i < 8; i++) mbar_init(bars + 8 * (B_OE + i), 1);
    for (int i = 0; i < 4; i++) mbar_init(bars + 8 * (B_REM + i), 1);
    for (int i = 0; i < 3; i++) mbar_init(bars + 8 * (B_OST + i), 8);
    for (int i = 0; i < 2; i++) mbar_init(bars + 8 * (B_WOF + i), 1);
    mbar_init(bars + 8 * B_GEMMD, 2);
    mbar_init(bars + 8 * B_EPI, 8);
    mbar_init(bars + 8 * B_H1ST, 2);
    mbar_init(bars + 8 * B_ATTD, 2);
    mbar_init(bars + 8 * B_GO, 1);
    mbar_init(bars + 8 * B_GO0, 1);
    mbar_init(bars + 8 * B_KV, 1);
    mbar_init(bars + 8 * B_X, 1);
    mbar_init(bars + 8 * (B_X + 1), 1);
    mbar_init(bars + 8 * B_FIN, 1);
    sts128(sb + SM_ZERO, 0u, 0u, 0u, 0u);
    fence_async_smem();
  }
  if (threadIdx.x == 384) {
    prefetch_tmap(&tm_x);
    prefetch_tmap(&tm_ww);
    prefetch_tmap(&tm_wn);
  }
  __syncthreads();

  if (warp >= 8 && warp < 12) {
    asm volatile("setmaxnreg.inc.sync.aligned.u32 144;");
    branch_a(sb, bars, warp - 8, lane, rb, g8, p, &tm_k, &tm_v, &tm_q, &tm_xt, &tm_z, &tm_out);
  } else if (warp < 8) {
    asm volatile("setmaxnreg.inc.sync.aligned.u32 168;");
    consumer_branch(sb, bars, warp >> 2, warp & 3, lane, rb, g8, rb3, g3, &tm_outh);
  } else {
    asm volatile("setmaxnreg.dec.sync.aligned.u32 32;");
    if (warp == 12) {
      producer(sb, bars, lane, rb, g8, rb3, g3, &tm_x, &tm_ww, &tm_wn);
    } else if (warp == 13) {
      store_agent(sb, bars, lane, rb, g8);
    } else if (warp == 14) {
      aux_warp(sb, lane, blockIdx.x, p);
    } else {
      unsigned ticket = 0;
      if (lane == 0) {
        ticket = atomicAdd(&g_ticket[64], 1u);
        prefetch_agent(bars, blockIdx.x, rb, g8, p, &tm_x, &tm_ww, &tm_wn, &tm_k, &tm_v);
      }
      o_loader(sb, bars, lane, rb, g8, rb3, 0, __shfl_sync(0xffffffffu, ticket, 0) / kNumCta + 1);
    }
  }
}

typedef CUresult (*EncodeTiledFn)(CUtensorMap*, CUtensorMapDataType, cuuint32_t, void*, const cuuint64_t*,
                                  const cuuint64_t*, const cuuint32_t*, const cuuint32_t*, CUtensorMapInterleave,
                                  CUtensorMapSwizzle, CUtensorMapL2promotion, CUtensorMapFloatOOBfill);

void make_map(EncodeTiledFn fn, CUtensorMap* tm, const void* ptr, int rank, const cuuint64_t* dims,
              const cuuint64_t* strides, const cuuint32_t* box, CUtensorMapSwizzle swz) {
  const cuuint32_t es[3] = {1, 1, 1};
  fn(tm, CU_TENSOR_MAP_DATA_TYPE_BFLOAT16, rank, const_cast<void*>(ptr), dims, strides, box, es,
     CU_TENSOR_MAP_INTERLEAVE_NONE, swz, CU_TENSOR_MAP_L2_PROMOTION_L2_128B, CU_TENSOR_MAP_FLOAT_OOB_FILL_NONE);
}
void make_map_2d(EncodeTiledFn fn, CUtensorMap* tm, const void* ptr, uint64_t inner, uint64_t outer, uint32_t bi,
                 uint32_t bo, CUtensorMapSwizzle swz) {
  const cuuint64_t dims[2] = {inner, outer};
  const cuuint64_t strides[1] = {inner * 2};
  const cuuint32_t box[2] = {bi, bo};
  make_map(fn, tm, ptr, 2, dims, strides, box, swz);
}

}

extern "C" void kernel_launch(void* const* d_in, const int* in_sizes, int n_in, void* d_out, int out_size) {
  (void)in_sizes; (void)n_in; (void)out_size;
  static EncodeTiledFn encode = nullptr;
  static void* zt_ptr = nullptr;
  static void* xt_ptr = nullptr;
  if (!encode) {
    void* fn = nullptr;
    cudaDriverEntryPointQueryResult qr;
    cudaGetDriverEntryPoint("cuTensorMapEncodeTiled", &fn, cudaEnableDefault, &qr);
    encode = (EncodeTiledFn)fn;
    cudaGetSymbolAddress(&zt_ptr, g_zt);
    cudaGetSymbolAddress(&xt_ptr, g_xt);
    cudaFuncSetAttribute(h3_swa_fused_kernel, cudaFuncAttributeMaxDynamicSharedMemorySize, SM_TOTAL);
  }
  Params p;
  p.aq = (const __nv_bfloat16*)d_in[0];
  p.ak = (const __nv_bfloat16*)d_in[1];
  p.av = (const __nv_bfloat16*)d_in[2];
  p.shift_k = (const __nv_bfloat16*)d_in[3];
  p.ssm_k = (const __nv_bfloat16*)d_in[4];
  p.ssm_d = (const __nv_bfloat16*)d_in[5];
  p.x = (const __nv_bfloat16*)d_in[6];
  p.wqkv = (const __nv_bfloat16*)d_in[7];
  p.wo = (const __nv_bfloat16*)d_in[8];

  CUtensorMap tm_x, tm_ww, tm_wn, tm_k, tm_v, tm_q, tm_xt, tm_z, tm_out, tm_outh;
  make_map_2d(encode, &tm_x, p.x, 640, 2048, 64, 128, CU_TENSOR_MAP_SWIZZLE_128B);
  {
    const cuuint64_t dims[3] = {640, 640, 3};
    const cuuint64_t strides[2] = {3840, 1280};
    const cuuint32_t boxw[3] = {64, 64, 3};
    const cuuint32_t boxn[3] = {16, 64, 3};
    make_map(encode, &tm_ww, p.wqkv, 3, dims, strides, boxw, CU_TENSOR_MAP_SWIZZLE_128B);
    make_map(encode, &tm_wn, p.wqkv, 3, dims, strides, boxn, CU_TENSOR_MAP_SWIZZLE_32B);
  }
  make_map_2d(encode, &tm_k, p.ak, 640, 2048, 80, 132, CU_TENSOR_MAP_SWIZZLE_NONE);
  make_map_2d(encode, &tm_v, p.av, 640, 2048, 80, 128, CU_TENSOR_MAP_SWIZZLE_NONE);
  make_map_2d(encode, &tm_q, p.aq, 640, 2048, 80, 128, CU_TENSOR_MAP_SWIZZLE_NONE);
  {
    const cuuint64_t dims[3] = {1024, 2, 640};
    const cuuint64_t strides[2] = {2048, 4096};
    const cuuint32_t box[3] = {64, 2, 80};
    make_map(encode, &tm_xt, xt_ptr, 3, dims, strides, box, CU_TENSOR_MAP_SWIZZLE_128B);
  }
  make_map_2d(encode, &tm_z, zt_ptr, 2048, 640, 64, 80, CU_TENSOR_MAP_SWIZZLE_128B);
  make_map_2d(encode, &tm_out, d_out, 1280, 2048, 80, 32, CU_TENSOR_MAP_SWIZZLE_NONE);
  make_map_2d(encode, &tm_outh, d_out, 1280, 2048, 80, 64, CU_TENSOR_MAP_SWIZZLE_NONE);

  h3_swa_fused_kernel<<<kNumCta, kThreads, SM_TOTAL, cudaStreamPerThread>>>(tm_x, tm_ww, tm_wn, tm_k, tm_v, tm_q, tm_xt,
                                                                          tm_z, tm_out, tm_outh, p);
}
```
